```python
import torch

def _softmax(x, axis=-1):
    return torch.softmax(x, dim=axis)
def _gelu(x):
    return torch.nn.functional.gelu(x, approximate="tanh")
def _silu(x):
    return torch.nn.functional.silu(x)
def _sigmoid(x):
    return torch.sigmoid(x)
def _layernorm(x, axis=-1, eps=1e-5):
    m = x.mean(dim=axis, keepdim=True)
    v = x.var(dim=axis, keepdim=True, unbiased=False)
    return (x - m) / torch.sqrt(v + eps)
def _scatter_add(tgt, idx, src, axis=0):
    return tgt.clone().index_add_(axis, idx, src)
def _segment_sum(src, seg, n):
    out = torch.zeros((n,) + src.shape[1:], dtype=src.dtype)
    return out.index_add_(0, seg, src)
def _pad(x, pw):
    flat = tuple(v for pair in reversed(pw) for v in pair)
    return torch.nn.functional.pad(x, flat)

kernel_name = 'concat_heads__mha_block__linear_attn_block__prompt'

def setup_inputs():

    _w = (lambda a: (lambda t: t.to(torch.bfloat16) if t.is_floating_point() else t)(torch.as_tensor(a)))
    def _A_setup():
        B, S, D, H = 1, 2048, 1024, 32
        return {
            "x": _w((lambda *s: torch.randn(*s, dtype=torch.bfloat16) * 0.2)(B, S, D)),
            "wqkv": _w((lambda *s: torch.randn(*s, dtype=torch.bfloat16) * 0.2)(D, 3 * D)),
            "wo": _w((lambda *s: torch.randn(*s, dtype=torch.bfloat16) * 0.05)(D, D)),
        }
    _A_in = _A_setup()

    def _B_setup():
        B, S, D = 1, 2048, 1024
        return {
            "x": _w((lambda *s: torch.randn(*s, dtype=torch.bfloat16) * 0.05)(B, S, D)),
            "wqkv": _w((lambda *s: torch.randn(*s, dtype=torch.bfloat16) * 1.6)(D, 3 * D)),
            "wo": _w((lambda *s: torch.randn(*s, dtype=torch.bfloat16) * 0.1)(D, D)),
        }
    _B_in = _B_setup()

    return {
        "A_x": _A_in["x"],
        "A_wqkv": _A_in["wqkv"],
        "A_wo": _A_in["wo"],
        "B_x": _B_in["x"],
        "B_wqkv": _B_in["wqkv"],
        "B_wo": _B_in["wo"],
    }

def reference(A_x, A_wqkv, A_wo, B_x, B_wqkv, B_wo):
    def _A_ref(x, wqkv, wo):
        B, S, D = x.shape
        H = 32
        Dh = D // H
        qkv = (lambda x, *d: x.permute(*d))((x @ wqkv).reshape(B, S, 3, H, Dh), 2, 0, 3, 1, 4)
        q, k, v = qkv[0], qkv[1], qkv[2]
        scores = torch.einsum("bhqd,bhkd->bhqk", q, k) * (Dh ** -0.5)
        p = _softmax(scores, axis=-1)
        o = torch.einsum("bhqk,bhkd->bhqd", p, v)
        return (lambda x, *d: x.permute(*d))(o, 0, 2, 1, 3).reshape(B, S, D) @ wo

    def _B_ref(x, wqkv, wo):
        B, S, D = x.shape
        H = 32; Dh = D // H
        qkv = (lambda x, *d: x.permute(*d))((x @ wqkv).reshape(B, S, 3, H, Dh), 2, 0, 3, 1, 4)
        q, k, v = qkv[0], qkv[1], qkv[2]
        phi = lambda t: torch.where(t > 0, t + 1, torch.exp(t)) + 1e-6
        pq, pk = phi(q), phi(k)
        kv = torch.einsum("bhsd,bhse->bhde", pk, v)
        z = torch.einsum("bhsd->bhd", pk)
        num = torch.einsum("bhqd,bhde->bhqe", pq, kv)
        den = torch.einsum("bhqd,bhd->bhq", pq, z)[..., None] + 1e-6
        o = num / den
        return (lambda x, *d: x.permute(*d))(o, 0, 2, 1, 3).reshape(B, S, D) @ wo

    a = _A_ref(A_x, A_wqkv, A_wo)
    b = _B_ref(B_x, B_wqkv, B_wo)
    return torch.concatenate([a, b], axis=-1)
```

```cpp
#define ATT_NWG 4
#define ATT_BN 64
#define ATT_CREGS 112
#define ATT_PREGS 32
template <uint32_t HB>
__device__ __forceinline__ void wgmma_rs_n128_z(float (&d)[64], uint32_t a0, uint32_t a1, uint32_t a2, uint32_t a3, uint32_t lb) {
  asm volatile("{\n.reg .pred p;\n.reg .b64 db;\n"
    "mov.b64 db, {%68, %69};\n"
    "setp.ne.b32 p, 0, 0;\n"
    "wgmma.mma_async.sync.aligned.m64n128k16.f32.bf16.bf16 "
    "{%0, %1, %2, %3, %4, %5, %6, %7, %8, %9, %10, %11, %12, %13, %14, %15, "
    "%16, %17, %18, %19, %20, %21, %22, %23, %24, %25, %26, %27, %28, %29, %30, %31, "
    "%32, %33, %34, %35, %36, %37, %38, %39, %40, %41, %42, %43, %44, %45, %46, %47, "
    "%48, %49, %50, %51, %52, %53, %54, %55, %56, %57, %58, %59, %60, %61, %62, %63}, "
    "{%64, %65, %66, %67}, db, p, 1, 1, 0;\n}\n"
    : "=f"(d[0]), "=f"(d[1]), "=f"(d[2]), "=f"(d[3]), "=f"(d[4]), "=f"(d[5]), "=f"(d[6]), "=f"(d[7]),
      "=f"(d[8]), "=f"(d[9]), "=f"(d[10]), "=f"(d[11]), "=f"(d[12]), "=f"(d[13]), "=f"(d[14]), "=f"(d[15]),
      "=f"(d[16]), "=f"(d[17]), "=f"(d[18]), "=f"(d[19]), "=f"(d[20]), "=f"(d[21]), "=f"(d[22]), "=f"(d[23]),
      "=f"(d[24]), "=f"(d[25]), "=f"(d[26]), "=f"(d[27]), "=f"(d[28]), "=f"(d[29]), "=f"(d[30]), "=f"(d[31]),
      "=f"(d[32]), "=f"(d[33]), "=f"(d[34]), "=f"(d[35]), "=f"(d[36]), "=f"(d[37]), "=f"(d[38]), "=f"(d[39]),
      "=f"(d[40]), "=f"(d[41]), "=f"(d[42]), "=f"(d[43]), "=f"(d[44]), "=f"(d[45]), "=f"(d[46]), "=f"(d[47]),
      "=f"(d[48]), "=f"(d[49]), "=f"(d[50]), "=f"(d[51]), "=f"(d[52]), "=f"(d[53]), "=f"(d[54]), "=f"(d[55]),
      "=f"(d[56]), "=f"(d[57]), "=f"(d[58]), "=f"(d[59]), "=f"(d[60]), "=f"(d[61]), "=f"(d[62]), "=f"(d[63])
    : "r"(a0), "r"(a1), "r"(a2), "r"(a3), "r"(lb), "n"(HB));
}
template <uint32_t HB>
__device__ __forceinline__ void wgmma_rs_n128(float (&d)[64], uint32_t a0, uint32_t a1, uint32_t a2, uint32_t a3, uint32_t lb) {
  asm volatile("{\n.reg .pred p;\n.reg .b64 db;\n"
    "mov.b64 db, {%68, %69};\n"
    "setp.ne.b32 p, 1, 0;\n"
    "wgmma.mma_async.sync.aligned.m64n128k16.f32.bf16.bf16 "
    "{%0, %1, %2, %3, %4, %5, %6, %7, %8, %9, %10, %11, %12, %13, %14, %15, "
    "%16, %17, %18, %19, %20, %21, %22, %23, %24, %25, %26, %27, %28, %29, %30, %31, "
    "%32, %33, %34, %35, %36, %37, %38, %39, %40, %41, %42, %43, %44, %45, %46, %47, "
    "%48, %49, %50, %51, %52, %53, %54, %55, %56, %57, %58, %59, %60, %61, %62, %63}, "
    "{%64, %65, %66, %67}, db, p, 1, 1, 0;\n}\n"
    : "+f"(d[0]), "+f"(d[1]), "+f"(d[2]), "+f"(d[3]), "+f"(d[4]), "+f"(d[5]), "+f"(d[6]), "+f"(d[7]),
      "+f"(d[8]), "+f"(d[9]), "+f"(d[10]), "+f"(d[11]), "+f"(d[12]), "+f"(d[13]), "+f"(d[14]), "+f"(d[15]),
      "+f"(d[16]), "+f"(d[17]), "+f"(d[18]), "+f"(d[19]), "+f"(d[20]), "+f"(d[21]), "+f"(d[22]), "+f"(d[23]),
      "+f"(d[24]), "+f"(d[25]), "+f"(d[26]), "+f"(d[27]), "+f"(d[28]), "+f"(d[29]), "+f"(d[30]), "+f"(d[31]),
      "+f"(d[32]), "+f"(d[33]), "+f"(d[34]), "+f"(d[35]), "+f"(d[36]), "+f"(d[37]), "+f"(d[38]), "+f"(d[39]),
      "+f"(d[40]), "+f"(d[41]), "+f"(d[42]), "+f"(d[43]), "+f"(d[44]), "+f"(d[45]), "+f"(d[46]), "+f"(d[47]),
      "+f"(d[48]), "+f"(d[49]), "+f"(d[50]), "+f"(d[51]), "+f"(d[52]), "+f"(d[53]), "+f"(d[54]), "+f"(d[55]),
      "+f"(d[56]), "+f"(d[57]), "+f"(d[58]), "+f"(d[59]), "+f"(d[60]), "+f"(d[61]), "+f"(d[62]), "+f"(d[63])
    : "r"(a0), "r"(a1), "r"(a2), "r"(a3), "r"(lb), "n"(HB));
}
template <uint32_t HB>
__device__ __forceinline__ void wgmma_rs_n64_z(float (&d)[32], uint32_t a0, uint32_t a1, uint32_t a2, uint32_t a3, uint32_t lb) {
  asm volatile("{\n.reg .pred p;\n.reg .b64 db;\n"
    "mov.b64 db, {%36, %37};\n"
    "setp.ne.b32 p, 0, 0;\n"
    "wgmma.mma_async.sync.aligned.m64n64k16.f32.bf16.bf16 "
    "{%0, %1, %2, %3, %4, %5, %6, %7, %8, %9, %10, %11, %12, %13, %14, %15, "
    "%16, %17, %18, %19, %20, %21, %22, %23, %24, %25, %26, %27, %28, %29, %30, %31}, "
    "{%32, %33, %34, %35}, db, p, 1, 1, 0;\n}\n"
    : "=f"(d[0]), "=f"(d[1]), "=f"(d[2]), "=f"(d[3]), "=f"(d[4]), "=f"(d[5]), "=f"(d[6]), "=f"(d[7]),
      "=f"(d[8]), "=f"(d[9]), "=f"(d[10]), "=f"(d[11]), "=f"(d[12]), "=f"(d[13]), "=f"(d[14]), "=f"(d[15]),
      "=f"(d[16]), "=f"(d[17]), "=f"(d[18]), "=f"(d[19]), "=f"(d[20]), "=f"(d[21]), "=f"(d[22]), "=f"(d[23]),
      "=f"(d[24]), "=f"(d[25]), "=f"(d[26]), "=f"(d[27]), "=f"(d[28]), "=f"(d[29]), "=f"(d[30]), "=f"(d[31])
    : "r"(a0), "r"(a1), "r"(a2), "r"(a3), "r"(lb), "n"(HB));
}
template <uint32_t HB>
__device__ __forceinline__ void wgmma_rs_n64(float (&d)[32], uint32_t a0, uint32_t a1, uint32_t a2, uint32_t a3, uint32_t lb) {
  asm volatile("{\n.reg .pred p;\n.reg .b64 db;\n"
    "mov.b64 db, {%36, %37};\n"
    "setp.ne.b32 p, 1, 0;\n"
    "wgmma.mma_async.sync.aligned.m64n64k16.f32.bf16.bf16 "
    "{%0, %1, %2, %3, %4, %5, %6, %7, %8, %9, %10, %11, %12, %13, %14, %15, "
    "%16, %17, %18, %19, %20, %21, %22, %23, %24, %25, %26, %27, %28, %29, %30, %31}, "
    "{%32, %33, %34, %35}, db, p, 1, 1, 0;\n}\n"
    : "+f"(d[0]), "+f"(d[1]), "+f"(d[2]), "+f"(d[3]), "+f"(d[4]), "+f"(d[5]), "+f"(d[6]), "+f"(d[7]),
      "+f"(d[8]), "+f"(d[9]), "+f"(d[10]), "+f"(d[11]), "+f"(d[12]), "+f"(d[13]), "+f"(d[14]), "+f"(d[15]),
      "+f"(d[16]), "+f"(d[17]), "+f"(d[18]), "+f"(d[19]), "+f"(d[20]), "+f"(d[21]), "+f"(d[22]), "+f"(d[23]),
      "+f"(d[24]), "+f"(d[25]), "+f"(d[26]), "+f"(d[27]), "+f"(d[28]), "+f"(d[29]), "+f"(d[30]), "+f"(d[31])
    : "r"(a0), "r"(a1), "r"(a2), "r"(a3), "r"(lb), "n"(HB));
}
template <uint32_t HB>
__device__ __forceinline__ void wgmma_rs_n32_z(float (&d)[16], uint32_t a0, uint32_t a1, uint32_t a2, uint32_t a3, uint32_t lb) {
  asm volatile("{\n.reg .pred p;\n.reg .b64 db;\n"
    "mov.b64 db, {%20, %21};\n"
    "setp.ne.b32 p, 0, 0;\n"
    "wgmma.mma_async.sync.aligned.m64n32k16.f32.bf16.bf16 "
    "{%0, %1, %2, %3, %4, %5, %6, %7, %8, %9, %10, %11, %12, %13, %14, %15}, "
    "{%16, %17, %18, %19}, db, p, 1, 1, 0;\n}\n"
    : "=f"(d[0]), "=f"(d[1]), "=f"(d[2]), "=f"(d[3]), "=f"(d[4]), "=f"(d[5]), "=f"(d[6]), "=f"(d[7]),
      "=f"(d[8]), "=f"(d[9]), "=f"(d[10]), "=f"(d[11]), "=f"(d[12]), "=f"(d[13]), "=f"(d[14]), "=f"(d[15])
    : "r"(a0), "r"(a1), "r"(a2), "r"(a3), "r"(lb), "n"(HB));
}
template <uint32_t HB>
__device__ __forceinline__ void wgmma_rs_n32(float (&d)[16], uint32_t a0, uint32_t a1, uint32_t a2, uint32_t a3, uint32_t lb) {
  asm volatile("{\n.reg .pred p;\n.reg .b64 db;\n"
    "mov.b64 db, {%20, %21};\n"
    "setp.ne.b32 p, 1, 0;\n"
    "wgmma.mma_async.sync.aligned.m64n32k16.f32.bf16.bf16 "
    "{%0, %1, %2, %3, %4, %5, %6, %7, %8, %9, %10, %11, %12, %13, %14, %15}, "
    "{%16, %17, %18, %19}, db, p, 1, 1, 0;\n}\n"
    : "+f"(d[0]), "+f"(d[1]), "+f"(d[2]), "+f"(d[3]), "+f"(d[4]), "+f"(d[5]), "+f"(d[6]), "+f"(d[7]),
      "+f"(d[8]), "+f"(d[9]), "+f"(d[10]), "+f"(d[11]), "+f"(d[12]), "+f"(d[13]), "+f"(d[14]), "+f"(d[15])
    : "r"(a0), "r"(a1), "r"(a2), "r"(a3), "r"(lb), "n"(HB));
}
template <uint32_t HB>
__device__ __forceinline__ void wgmma_rs_n40_tb(float (&d)[20], uint32_t a0, uint32_t a1, uint32_t a2, uint32_t a3, uint32_t lb) {
  asm volatile("{\n.reg .pred p;\n.reg .b64 db;\n"
    "mov.b64 db, {%24, %25};\n"
    "setp.ne.b32 p, 1, 0;\n"
    "wgmma.mma_async.sync.aligned.m64n40k16.f32.bf16.bf16 "
    "{%0, %1, %2, %3, %4, %5, %6, %7, %8, %9, %10, %11, %12, %13, %14, %15, "
    "%16, %17, %18, %19}, "
    "{%20, %21, %22, %23}, db, p, 1, 1, 1;\n}\n"
    : "+f"(d[0]), "+f"(d[1]), "+f"(d[2]), "+f"(d[3]), "+f"(d[4]), "+f"(d[5]), "+f"(d[6]), "+f"(d[7]),
      "+f"(d[8]), "+f"(d[9]), "+f"(d[10]), "+f"(d[11]), "+f"(d[12]), "+f"(d[13]), "+f"(d[14]), "+f"(d[15]),
      "+f"(d[16]), "+f"(d[17]), "+f"(d[18]), "+f"(d[19])
    : "r"(a0), "r"(a1), "r"(a2), "r"(a3), "r"(lb), "n"(HB));
}
template <uint32_t HB>
__device__ __forceinline__ void wgmma_rs_n40_tb_z(float (&d)[20], uint32_t a0, uint32_t a1, uint32_t a2, uint32_t a3, uint32_t lb) {
  asm volatile("{\n.reg .pred p;\n.reg .b64 db;\n"
    "mov.b64 db, {%24, %25};\n"
    "setp.ne.b32 p, 0, 0;\n"
    "wgmma.mma_async.sync.aligned.m64n40k16.f32.bf16.bf16 "
    "{%0, %1, %2, %3, %4, %5, %6, %7, %8, %9, %10, %11, %12, %13, %14, %15, "
    "%16, %17, %18, %19}, "
    "{%20, %21, %22, %23}, db, p, 1, 1, 1;\n}\n"
    : "=f"(d[0]), "=f"(d[1]), "=f"(d[2]), "=f"(d[3]), "=f"(d[4]), "=f"(d[5]), "=f"(d[6]), "=f"(d[7]),
      "=f"(d[8]), "=f"(d[9]), "=f"(d[10]), "=f"(d[11]), "=f"(d[12]), "=f"(d[13]), "=f"(d[14]), "=f"(d[15]),
      "=f"(d[16]), "=f"(d[17]), "=f"(d[18]), "=f"(d[19])
    : "r"(a0), "r"(a1), "r"(a2), "r"(a3), "r"(lb), "n"(HB));
}
template <uint32_t HB>
__device__ __forceinline__ void wgmma_rs_n32_tb(float (&d)[16], uint32_t a0, uint32_t a1, uint32_t a2, uint32_t a3, uint32_t lb) {
  asm volatile("{\n.reg .pred p;\n.reg .b64 db;\n"
    "mov.b64 db, {%20, %21};\n"
    "setp.ne.b32 p, 1, 0;\n"
    "wgmma.mma_async.sync.aligned.m64n32k16.f32.bf16.bf16 "
    "{%0, %1, %2, %3, %4, %5, %6, %7, %8, %9, %10, %11, %12, %13, %14, %15}, "
    "{%16, %17, %18, %19}, db, p, 1, 1, 1;\n}\n"
    : "+f"(d[0]), "+f"(d[1]), "+f"(d[2]), "+f"(d[3]), "+f"(d[4]), "+f"(d[5]), "+f"(d[6]), "+f"(d[7]),
      "+f"(d[8]), "+f"(d[9]), "+f"(d[10]), "+f"(d[11]), "+f"(d[12]), "+f"(d[13]), "+f"(d[14]), "+f"(d[15])
    : "r"(a0), "r"(a1), "r"(a2), "r"(a3), "r"(lb), "n"(HB));
}
template <uint32_t HB>
__device__ __forceinline__ void wgmma_rs_n32_tb_z(float (&d)[16], uint32_t a0, uint32_t a1, uint32_t a2, uint32_t a3, uint32_t lb) {
  asm volatile("{\n.reg .pred p;\n.reg .b64 db;\n"
    "mov.b64 db, {%20, %21};\n"
    "setp.ne.b32 p, 0, 0;\n"
    "wgmma.mma_async.sync.aligned.m64n32k16.f32.bf16.bf16 "
    "{%0, %1, %2, %3, %4, %5, %6, %7, %8, %9, %10, %11, %12, %13, %14, %15}, "
    "{%16, %17, %18, %19}, db, p, 1, 1, 1;\n}\n"
    : "=f"(d[0]), "=f"(d[1]), "=f"(d[2]), "=f"(d[3]), "=f"(d[4]), "=f"(d[5]), "=f"(d[6]), "=f"(d[7]),
      "=f"(d[8]), "=f"(d[9]), "=f"(d[10]), "=f"(d[11]), "=f"(d[12]), "=f"(d[13]), "=f"(d[14]), "=f"(d[15])
    : "r"(a0), "r"(a1), "r"(a2), "r"(a3), "r"(lb), "n"(HB));
}
template <uint32_t HA, uint32_t HB>
__device__ __forceinline__ void wgmma_ss_n72_tb_ta(float (&d)[36], uint32_t la, uint32_t lb) {
  asm volatile("{\n.reg .pred p;\n.reg .b64 da, db;\n"
    "mov.b64 da, {%36, %38};\nmov.b64 db, {%37, %39};\n"
    "setp.ne.b32 p, 1, 0;\n"
    "wgmma.mma_async.sync.aligned.m64n72k16.f32.bf16.bf16 "
    "{%0, %1, %2, %3, %4, %5, %6, %7, %8, %9, %10, %11, %12, %13, %14, %15, "
    "%16, %17, %18, %19, %20, %21, %22, %23, %24, %25, %26, %27, %28, %29, %30, %31, "
    "%32, %33, %34, %35}, "
    "da, db, p, 1, 1, 1, 1;\n}\n"
    : "+f"(d[0]), "+f"(d[1]), "+f"(d[2]), "+f"(d[3]), "+f"(d[4]), "+f"(d[5]), "+f"(d[6]), "+f"(d[7]),
      "+f"(d[8]), "+f"(d[9]), "+f"(d[10]), "+f"(d[11]), "+f"(d[12]), "+f"(d[13]), "+f"(d[14]), "+f"(d[15]),
      "+f"(d[16]), "+f"(d[17]), "+f"(d[18]), "+f"(d[19]), "+f"(d[20]), "+f"(d[21]), "+f"(d[22]), "+f"(d[23]),
      "+f"(d[24]), "+f"(d[25]), "+f"(d[26]), "+f"(d[27]), "+f"(d[28]), "+f"(d[29]), "+f"(d[30]), "+f"(d[31]),
      "+f"(d[32]), "+f"(d[33]), "+f"(d[34]), "+f"(d[35])
    : "r"(la), "r"(lb), "n"(HA), "n"(HB));
}
template <uint32_t HA, uint32_t HB>
__device__ __forceinline__ void wgmma_ss_n72_tb_ta_z(float (&d)[36], uint32_t la, uint32_t lb) {
  asm volatile("{\n.reg .pred p;\n.reg .b64 da, db;\n"
    "mov.b64 da, {%36, %38};\nmov.b64 db, {%37, %39};\n"
    "setp.ne.b32 p, 0, 0;\n"
    "wgmma.mma_async.sync.aligned.m64n72k16.f32.bf16.bf16 "
    "{%0, %1, %2, %3, %4, %5, %6, %7, %8, %9, %10, %11, %12, %13, %14, %15, "
    "%16, %17, %18, %19, %20, %21, %22, %23, %24, %25, %26, %27, %28, %29, %30, %31, "
    "%32, %33, %34, %35}, "
    "da, db, p, 1, 1, 1, 1;\n}\n"
    : "=f"(d[0]), "=f"(d[1]), "=f"(d[2]), "=f"(d[3]), "=f"(d[4]), "=f"(d[5]), "=f"(d[6]), "=f"(d[7]),
      "=f"(d[8]), "=f"(d[9]), "=f"(d[10]), "=f"(d[11]), "=f"(d[12]), "=f"(d[13]), "=f"(d[14]), "=f"(d[15]),
      "=f"(d[16]), "=f"(d[17]), "=f"(d[18]), "=f"(d[19]), "=f"(d[20]), "=f"(d[21]), "=f"(d[22]), "=f"(d[23]),
      "=f"(d[24]), "=f"(d[25]), "=f"(d[26]), "=f"(d[27]), "=f"(d[28]), "=f"(d[29]), "=f"(d[30]), "=f"(d[31]),
      "=f"(d[32]), "=f"(d[33]), "=f"(d[34]), "=f"(d[35])
    : "r"(la), "r"(lb), "n"(HA), "n"(HB));
}

constexpr int SEQ = 2048, DM = 1024, NH = 32, DH = 32;

__device__ __align__(1024) __nv_bfloat16 g_qkv[3 * NH * SEQ * DH];
__device__ __align__(1024) __nv_bfloat16 g_oA[SEQ * DM];
__device__ __align__(1024) __nv_bfloat16 g_pq[SEQ * DM];
__device__ __align__(1024) __nv_bfloat16 g_oB[SEQ * DM];
__device__ __align__(16) float g_stats[3 * NH * 128];
__device__ __align__(16) float g_kv[NH * 32 * 40];

constexpr int G_BK = 32;
constexpr int G_STAGES = 6;
constexpr int G_A_BYTES = 128 * G_BK * 2;
constexpr int G_B_BYTES = 256 * G_BK * 2;
constexpr int G_STAGE_BYTES = G_A_BYTES + G_B_BYTES;
constexpr int G_STG_OFF = G_STAGES * G_STAGE_BYTES;
constexpr int G_ONES_OFF = G_STG_OFF + 65536;
constexpr int G_BAR_OFF = G_ONES_OFF + 2048;
constexpr int G_SMEM = G_BAR_OFF + 256 + 1024;
constexpr int G_KT = DM / G_BK;

enum { EPI_AQ = 0, EPI_AK = 1, EPI_AV = 2, EPI_BQ = 3, EPI_BKV = 4, EPI_OUT = 5 };

struct TileInfo {
  int epi;
  int branch;
  int m0;
  int nblk;
  int ncol;
};

constexpr float QSCALE = 0.17677669529663687f * 1.4426950408889634f;
constexpr float LOG2E = 1.4426950408889634f;

template <int MODE> __device__ __forceinline__ int num_pair_tiles() { return MODE == 0 ? 192 : 64; }

template <int MODE> __device__ __forceinline__ TileInfo decode_tile(int t, int rank) {
  TileInfo ti;
  if (MODE == 0) {
    if (t < 64) {
      int mp = t & 7, j = t >> 3;
      ti.epi = EPI_BKV; ti.branch = 1; ti.m0 = mp * 256 + rank * 128;
      ti.nblk = (rank == 0 ? 16 : 32) + 2 * j;
      ti.ncol = 4 * j;
    } else if (t < 96) {
      int u = t - 64, mp = u & 7, nt = u >> 3;
      ti.epi = EPI_BQ; ti.branch = 1; ti.m0 = mp * 256 + rank * 128;
      ti.nblk = nt * 4 + rank * 2;
      ti.ncol = nt * 256;
    } else {
      int u = t - 96, mp = u & 7, nt = u >> 3;
      ti.epi = nt >> 2; ti.branch = 0; ti.m0 = mp * 256 + rank * 128;
      ti.nblk = nt * 4 + rank * 2;
      ti.ncol = (nt & 3) * 8;
    }
  } else {
    int br = t >> 5, u = t & 31, mp = u & 7, nt = u >> 3;
    ti.epi = EPI_OUT; ti.branch = br; ti.m0 = mp * 256 + rank * 128;
    ti.nblk = nt * 4 + rank * 2;
    ti.ncol = br * DM + nt * 256;
  }
  return ti;
}

__device__ __forceinline__ float phi_fn(float t) {
  float e = ex2_approx(t * LOG2E);
  float y = t > 0.f ? t + 1.f : e;
  return y + 1e-6f;
}

struct GemmMaps {
  CUtensorMap a[2];
  CUtensorMap w[2];
  CUtensorMap st_head;
  CUtensorMap st_row;
};

#define TIM(k, i)
#define TIMG(k, i)

template <int MODE>
__global__ void __cluster_dims__(2, 1, 1) __launch_bounds__(384, 1)
gemm_kernel(const __grid_constant__ GemmMaps maps) {
  extern __shared__ uint8_t smem_raw[];
  const uint32_t sb = (smem_u32(smem_raw) + 1023) & ~1023u;
  const uint32_t bar_full = sb + G_BAR_OFF, bar_empty = bar_full + 8 * G_STAGES;
  const int warp = uniform_warp_id(), lane = threadIdx.x & 31;
  const uint32_t rank = cluster_rank();
  const int pair = blockIdx.x >> 1, npairs = gridDim.x >> 1;

  if (threadIdx.x == 0) {
    for (int s = 0; s < G_STAGES; s++) {
      mbar_init(bar_full + 8 * s, 1);
      mbar_init(bar_empty + 8 * s, 4);
    }
    fence_mbar_init();
  }
  if (MODE == 0) {
    uint32_t* ones = reinterpret_cast<uint32_t*>(smem_raw + (sb - smem_u32(smem_raw)) + G_ONES_OFF);
    for (int i = threadIdx.x; i < 512; i += 384) ones[i] = 0x3F803F80u;
    fence_proxy_async_smem();
  }
  __syncthreads();
  cluster_sync();

  if (warp < 4) {
    reg_dealloc<40>();
    if (warp == 0 && lane == 0) {
      prefetch_tmap(&maps.a[0]); prefetch_tmap(&maps.a[1]);
      prefetch_tmap(&maps.w[0]); prefetch_tmap(&maps.w[1]);
      int stage = 0; uint32_t phase = 1;
      for (int t = pair; t < num_pair_tiles<MODE>(); t += npairs) {
        const TileInfo ti = decode_tile<MODE>(t, rank);
        const CUtensorMap* ma = &maps.a[ti.branch];
        const CUtensorMap* mw = &maps.w[ti.branch];
        for (int kt = 0; kt < G_KT; kt++) {
          mbar_wait(bar_empty + 8 * stage, phase);
          const uint32_t full = bar_full + 8 * stage;
          const uint32_t sa = sb + stage * G_STAGE_BYTES;
          mbar_expect_tx(full, G_STAGE_BYTES);
          tma_load_2d(sa, ma, full, kt * G_BK, ti.m0);
          tma_load_3d_mc(sa + G_A_BYTES + rank * (G_B_BYTES / 2), mw, full, 0, kt * G_BK, ti.nblk, (uint16_t)3);
          if (++stage == G_STAGES) { stage = 0; phase ^= 1; }
        }
      }
    }
    __syncwarp();
    cluster_sync();
  } else {
    reg_alloc<232>();
    const int wg = (warp >> 2) - 1;
    const int wq = warp & 3;
    const int tid = threadIdx.x & 127;
    const int qd = lane & 3, r8 = lane >> 2;
    int stage = 0; uint32_t phase = 0;
    float acc[128];
    const uint32_t stg = sb + G_STG_OFF + wg * 32768;
    int tcount = 0;
    TIM(MODE * 2, 0); TIMG(MODE * 2, 30);
    for (int t = pair; t < num_pair_tiles<MODE>(); t += npairs) {
      const TileInfo ti = decode_tile<MODE>(t, rank);
      int prev = stage;
      {
        mbar_wait(bar_full + 8 * stage, phase);
        TIM(MODE * 2, 1 + 3 * tcount);
        const uint32_t sa = sb + stage * G_STAGE_BYTES;
        const uint32_t da = desc_lo(sa + wg * 4096, 16), db = desc_lo(sa + G_A_BYTES, 4096);
        wg_fence();
        wgmma_ss_n256_tb_z<HI_SW64_512, HI_SW128_1024>(acc, da, db);
        wgmma_ss_n256_tb<HI_SW64_512, HI_SW128_1024>(acc, da + 2, db + 128);
        wg_commit();
        if (++stage == G_STAGES) { stage = 0; phase ^= 1; }
      }
#pragma unroll 1
      for (int kt = 1; kt < G_KT; kt++) {
        mbar_wait(bar_full + 8 * stage, phase);
        const uint32_t sa = sb + stage * G_STAGE_BYTES;
        const uint32_t da = desc_lo(sa + wg * 4096, 16), db = desc_lo(sa + G_A_BYTES, 4096);
        wg_fence();
        wgmma_ss_n256_tb<HI_SW64_512, HI_SW128_1024>(acc, da, db);
        wgmma_ss_n256_tb<HI_SW64_512, HI_SW128_1024>(acc, da + 2, db + 128);
        wg_commit();
        wg_wait<1>();
        if (tid < 2) mbar_arrive_cluster(bar_empty + 8 * prev, tid);
        prev = stage;
        if (++stage == G_STAGES) { stage = 0; phase ^= 1; }
      }
      wg_wait<0>();
      if (tid < 2) mbar_arrive_cluster(bar_empty + 8 * prev, tid);
      fence_regs(acc);
      TIM(MODE * 2, 2 + 3 * tcount);

      if (tid == 0) bulk_wait_read<0>();
      const int epi = ti.epi;
      if (MODE == 0 && epi <= EPI_AV) {
        named_bar_sync(1 + wg, 128);
        const float sc = epi == EPI_AQ ? QSCALE : 1.f;
        float* st = g_stats + (epi * NH + ti.ncol) * 128 + (ti.m0 >> 4) + wg * 4 + wq;
        const int row = wq * 16 + (lane & 7) + ((lane >> 3) & 1) * 8;
        const uint32_t a0 = stg + row * 64;
        const int sw = (row >> 1) & 3, ch = lane >> 4;
#pragma unroll
        for (int h = 0; h < 8; h++) {
          float s0 = 0.f, s1 = 0.f;
          uint32_t p[8];
#pragma unroll
          for (int j = 0; j < 4; j++) {
            const int b = (h * 4 + j) * 4;
            const float x0 = acc[b] * sc, x1 = acc[b + 1] * sc, x2 = acc[b + 2] * sc, x3 = acc[b + 3] * sc;
            s0 = fmaf(x0, x0, s0); s0 = fmaf(x1, x1, s0);
            s1 = fmaf(x2, x2, s1); s1 = fmaf(x3, x3, s1);
            p[2 * j] = pack_bf16(x0, x1);
            p[2 * j + 1] = pack_bf16(x2, x3);
          }
          stmatrix_x4(a0 + h * 4096 + ((ch ^ sw) << 4), p[0], p[1], p[2], p[3]);
          stmatrix_x4(a0 + h * 4096 + (((ch + 2) ^ sw) << 4), p[4], p[5], p[6], p[7]);
          s0 += __shfl_xor_sync(0xffffffffu, s0, 1);
          s1 += __shfl_xor_sync(0xffffffffu, s1, 1);
          s0 += __shfl_xor_sync(0xffffffffu, s0, 2);
          s1 += __shfl_xor_sync(0xffffffffu, s1, 2);
          float r;
          if (epi == EPI_AV) {
            r = s0 + s1;
            r += __shfl_xor_sync(0xffffffffu, r, 4);
            r += __shfl_xor_sync(0xffffffffu, r, 8);
            r += __shfl_xor_sync(0xffffffffu, r, 16);
          } else {
            r = (s0 > s1 || s0 != s0) ? s0 : s1;
#pragma unroll
            for (int o = 4; o < 32; o <<= 1) {
              const float u = __shfl_xor_sync(0xffffffffu, r, o);
              r = (r > u || r != r) ? r : u;
            }
          }
          if (lane == 0) st[h * 128] = r;
        }
        fence_proxy_async_smem();
        named_bar_sync(1 + wg, 128);
        if (tid == 0) {
          const int row0 = (epi * NH + ti.ncol) * SEQ + ti.m0 + wg * 64;
#pragma unroll
          for (int h = 0; h < 8; h++) tma_store_2d(&maps.st_head, stg + h * 4096, 0, row0 + h * SEQ);
          bulk_commit();
        }
      } else if (MODE == 1 || epi == EPI_BQ) {
        named_bar_sync(1 + wg, 128);
        const int row = wq * 16 + (lane & 7) + ((lane >> 3) & 1) * 8;
        const uint32_t a0 = stg + row * 128;
        const int sw = row & 7, ch = lane >> 4;
#pragma unroll
        for (int c = 0; c < 4; c++) {
#pragma unroll
          for (int jj = 0; jj < 4; jj++) {
            uint32_t p[4];
#pragma unroll
            for (int j = 0; j < 2; j++) {
              const int b = (c * 8 + jj * 2 + j) * 4;
              float x0 = acc[b], x1 = acc[b + 1], x2 = acc[b + 2], x3 = acc[b + 3];
              if (MODE == 0) { x0 = phi_fn(x0); x1 = phi_fn(x1); x2 = phi_fn(x2); x3 = phi_fn(x3); }
              p[2 * j] = pack_bf16(x0, x1);
              p[2 * j + 1] = pack_bf16(x2, x3);
            }
            stmatrix_x4(a0 + c * 8192 + (((jj * 2 + ch) ^ sw) << 4), p[0], p[1], p[2], p[3]);
          }
        }
        fence_proxy_async_smem();
        named_bar_sync(1 + wg, 128);
        if (tid == 0) {
#pragma unroll
          for (int c = 0; c < 4; c++) tma_store_2d(&maps.st_row, stg + c * 8192, ti.ncol + c * 64, ti.m0 + wg * 64);
          bulk_commit();
        }
      } else {
        named_bar_sync(3, 256);
        const uint32_t T = sb + G_STG_OFF;
        const int row = wg * 64 + wq * 16 + (lane & 7) + ((lane >> 3) & 1) * 8;
        const uint32_t a0 = T + row * 128;
        const int sw = row & 7, ch = lane >> 4;
#pragma unroll
        for (int c = 0; c < 4; c++) {
#pragma unroll
          for (int jj = 0; jj < 4; jj++) {
            uint32_t p[4];
#pragma unroll
            for (int j = 0; j < 2; j++) {
              const int b = (c * 8 + jj * 2 + j) * 4;
              float x0 = acc[b], x1 = acc[b + 1], x2 = acc[b + 2], x3 = acc[b + 3];
              if (c < 2) { x0 = phi_fn(x0); x1 = phi_fn(x1); x2 = phi_fn(x2); x3 = phi_fn(x3); }
              p[2 * j] = pack_bf16(x0, x1);
              p[2 * j + 1] = pack_bf16(x2, x3);
            }
            stmatrix_x4(a0 + c * 16384 + (((jj * 2 + ch) ^ sw) << 4), p[0], p[1], p[2], p[3]);
          }
        }
        fence_proxy_async_smem();
        named_bar_sync(3, 256);
        float d[36];
        const uint32_t ta = T + wg * 16384, tb = T + 32768 + wg * 16384, ones = sb + G_ONES_OFF;
        wg_fence();
#pragma unroll
        for (int k = 0; k < 8; k++) {
          const uint32_t da = desc_lo(ta + k * 2048, 16);
          const uint32_t db = desc_lo(tb + k * 2048, ones - (tb + k * 2048));
          if (k == 0) wgmma_ss_n72_tb_ta_z<HI_SW128_1024, HI_SW128_1024>(d, da, db);
          else wgmma_ss_n72_tb_ta<HI_SW128_1024, HI_SW128_1024>(d, da, db);
        }
        wg_commit();
        wg_wait<0>();
        fence_regs(d);
        const int head = ti.ncol + wg * 2 + (wq >> 1);
        float* kv = g_kv + (head * 32 + (wq & 1) * 16 + r8) * 40 + 2 * qd;
        const bool hi = wq >= 2;
#pragma unroll
        for (int j = 0; j < 4; j++) {
          const float v0 = hi ? d[16 + 4 * j] : d[4 * j], v1 = hi ? d[17 + 4 * j] : d[4 * j + 1];
          const float v2 = hi ? d[18 + 4 * j] : d[4 * j + 2], v3 = hi ? d[19 + 4 * j] : d[4 * j + 3];
          red_add_v2(kv + 8 * j, v0, v1);
          red_add_v2(kv + 8 * 40 + 8 * j, v2, v3);
        }
        red_add_v2(kv + 32, d[32], d[33]);
        red_add_v2(kv + 8 * 40 + 32, d[34], d[35]);
        named_bar_sync(3, 256);
      }
      TIM(MODE * 2, 3 + 3 * tcount);
      tcount++;
    }
    if (tid == 0) bulk_wait<0>();
    TIM(MODE * 2, 29); TIMG(MODE * 2, 31);
    if (MODE == 1 && blockIdx.x < 8) {
      for (int i = blockIdx.x * 256 + wg * 128 + tid; i < NH * 32 * 40; i += 8 * 256) g_kv[i] = 0.f;
    }
    __syncwarp();
    cluster_sync();
  }
}

#define ATT_DBUF 0
#define ATT_POLY_MASK 0x0000
#define ATT_DEG 5
#define ATT_PP 0

constexpr int A_STAGES = 8;
constexpr int A_STAGE_BYTES = 16384;
constexpr int A_ONES_OFF = A_STAGES * A_STAGE_BYTES;
constexpr int A_BAR_OFF = A_ONES_OFF + 1024;
constexpr int A_SMEM = A_BAR_OFF + 256 + 1024;
constexpr int A_ROWS = ATT_NWG * 64;
constexpr int A_ITEMS = NH * SEQ / A_ROWS;
constexpr int A_NSTG = SEQ / 128;

template <int DEG> __device__ __forceinline__ float ex2_poly(float x) {
  const float t = __fadd_rn(x, 12582912.f);
  const float f = __fadd_rn(x, -__fadd_rn(t, -12582912.f));
  float p;
  if (DEG == 3) {
    p = fmaf(5.517166853e-02f, f, 2.426111251e-01f);
    p = fmaf(p, f, 6.932609677e-01f);
    p = fmaf(p, f, 9.999280572e-01f);
  } else if (DEG == 4) {
    p = fmaf(9.570102207e-03f, f, 5.591785908e-02f);
    p = fmaf(p, f, 2.402474433e-01f);
    p = fmaf(p, f, 6.931217909e-01f);
    p = fmaf(p, f, 9.999992847e-01f);
  } else {
    p = fmaf(1.327793929e-03f, f, 9.675757959e-03f);
    p = fmaf(p, f, 5.550709739e-02f);
    p = fmaf(p, f, 2.402211428e-01f);
    p = fmaf(p, f, 6.931469440e-01f);
    p = fmaf(p, f, 1.000000119e+00f);
  }
  return __int_as_float(__float_as_int(p) + (__float_as_int(t) << 23));
}

template <int BN> struct QKmma;
template <> struct QKmma<128> {
  static __device__ __forceinline__ void run(float (&s)[64], const uint32_t (&q)[8], uint32_t dk) {
    wgmma_rs_n128_z<HI_SW64_512>(s, q[0], q[1], q[2], q[3], dk);
    wgmma_rs_n128<HI_SW64_512>(s, q[4], q[5], q[6], q[7], dk + 2);
  }
};
template <> struct QKmma<64> {
  static __device__ __forceinline__ void run(float (&s)[32], const uint32_t (&q)[8], uint32_t dk) {
    wgmma_rs_n64_z<HI_SW64_512>(s, q[0], q[1], q[2], q[3], dk);
    wgmma_rs_n64<HI_SW64_512>(s, q[4], q[5], q[6], q[7], dk + 2);
  }
};

template <int BN, int K0 = 0, int K1 = BN / 16>
__device__ __forceinline__ void pv_mma(float (&o)[20], const uint32_t (&p)[BN / 4], uint32_t v, uint32_t ones) {
  const uint32_t d0 = desc_lo(v, ones - v);
#pragma unroll
  for (int k = K0; k < K1; k++) {
    const uint32_t d = d0 + (uint32_t)(64 * k) - ((uint32_t)(64 * k) << 16);
    wgmma_rs_n40_tb<HI_SW64_512>(o, p[4 * k], p[4 * k + 1], p[4 * k + 2], p[4 * k + 3], d);
  }
}

template <int BN> __device__ __forceinline__ void exp_inplace(float (&s)[BN / 2]) {
#pragma unroll
  for (int i = 0; i < BN / 2; i++) {
    if ((ATT_POLY_MASK >> (i & 15)) & 1) s[i] = ex2_poly<ATT_DEG>(s[i]);
    else s[i] = ex2_approx(s[i]);
  }
}
template <int BN> __device__ __forceinline__ void pack_p(uint32_t (&p)[BN / 4], const float (&s)[BN / 2]) {
#pragma unroll
  for (int i = 0; i < BN / 4; i++) p[i] = pack_bf16(s[2 * i], s[2 * i + 1]);
}

template <int BN, int I0, int I1> __device__ __forceinline__ void exp_pack(uint32_t (&p)[BN / 4], const float (&s)[BN / 2]) {
#pragma unroll
  for (int i = I0; i < I1; i += 2) {
    const float a = ((ATT_POLY_MASK >> (i & 15)) & 1) ? ex2_poly<ATT_DEG>(s[i]) : ex2_approx(s[i]);
    const float b = ((ATT_POLY_MASK >> ((i + 1) & 15)) & 1) ? ex2_poly<ATT_DEG>(s[i + 1]) : ex2_approx(s[i + 1]);
    p[i >> 1] = pack_bf16(a, b);
  }
}

template <int NWG> __device__ __forceinline__ void pp_sync(int wg) { if (ATT_PP) named_bar_sync(4 + wg, 256); }
template <int NWG> __device__ __forceinline__ void pp_arrive(int wg) { if (ATT_PP) named_bar_arrive(4 + (wg + 1 == NWG ? 0 : wg + 1), 256); }

struct KVPipe {
  uint32_t base, full, empty;
  int stage; uint32_t phase;
  __device__ __forceinline__ void advance() { if (++stage == A_STAGES) { stage = 0; phase ^= 1; } }
};

#define ATT_DUMMY 0
#define ATT_DUMMY_DEPTH 2
#define ATT_DUMMY_WAIT 1
#define ATT_GREGS 168
__device__ unsigned long long g_dummy_cnt[132 * 2];
template <int NWG, int BN, int DBUF>
#define ATT_X4 0
#define ATT_THREADS (ATT_X4 ? (ATT_NWG + ATT_DUMMY) * 128 + 32 : (ATT_NWG + 1 + ATT_DUMMY) * 128)
#define ATT_LAUNCH_REGS ((65536 / ATT_THREADS) / 8 * 8 > 168 ? 168 : (65536 / ATT_THREADS) / 8 * 8)
__global__ void __launch_bounds__(ATT_THREADS, 1)
attn_kernel(const __grid_constant__ CUtensorMap tm_kv) {
  extern __shared__ uint8_t smem_raw[];
  const uint32_t sb = (smem_u32(smem_raw) + 1023) & ~1023u;
  const uint32_t bar_full = sb + A_BAR_OFF, bar_empty = bar_full + 8 * A_STAGES;
  const int warp = uniform_warp_id(), lane = threadIdx.x & 31;
  constexpr int NBLK = SEQ / BN;
  constexpr int BPS = 128 / BN;

  if (threadIdx.x == 0) {
    for (int s = 0; s < A_STAGES; s++) {
      mbar_init(bar_full + 8 * s, 1);
      mbar_init(bar_empty + 8 * s, NWG);
    }
    fence_mbar_init();
  }
  {
    uint32_t* ones = reinterpret_cast<uint32_t*>(smem_raw + (sb - smem_u32(smem_raw)) + A_ONES_OFF);
    if (threadIdx.x < 256) ones[threadIdx.x] = 0x3F803F80u;
    fence_proxy_async_smem();
  }
  __shared__ volatile int s_done;
  if (threadIdx.x == 0) s_done = 0;
  __syncthreads();

  const int role = ATT_X4 ? (warp < 4 * NWG ? 1 : (warp < 4 * (NWG + ATT_DUMMY) ? 2 : 0))
                          : (warp < 4 ? 0 : (warp < 4 * (NWG + 1) ? 1 : 2));
  if (ATT_DUMMY && role == 2) {
    reg_alloc<ATT_GREGS>();
#define ATT_DN 128
    float acc0[ATT_DN / 2], acc1[ATT_DN / 2];
#pragma unroll
    for (int i = 0; i < ATT_DN / 2; i++) { acc0[i] = 0.f; acc1[i] = 0.f; }
    unsigned long long n = 0;
    const uint32_t da = desc_lo(sb, 16), db = desc_lo(sb + 16384, ATT_DN == 128 ? 4096 : 2048);
    long long t0 = clock64();
    while (true) {
      if ((n & 15) == 0) {
        uint32_t cnt;
        asm volatile("{\n.reg .pred p;\nsetp.ge.s32 p, %1, %2;\nbarrier.cta.red.popc.aligned.u32 %0, %3, 128, p;\n}" : "=r"(cnt) : "r"((int)s_done), "r"(NWG), "r"(8 + ((warp >> 2) & 1)) : "memory");
        if (cnt) break;
      }
      wg_fence();
#pragma unroll
      for (int r = 0; r < ATT_DUMMY_DEPTH; r++) {
        wgmma_ss_n128_tb<HI_SW64_512, HI_SW128_1024>(acc0, da + 2 * (r & 1), db + 128 * (r & 1));
        wgmma_ss_n128_tb<HI_SW64_512, HI_SW128_1024>(acc1, da + 2 * (r & 1), db + 512 + 128 * (r & 1));
      }
      wg_commit();
      wg_wait<ATT_DUMMY_WAIT>();
      n += ATT_DUMMY_DEPTH;
    }
    wg_wait<0>();
    long long t1 = clock64();
    float r = 0.f;
#pragma unroll
    for (int i = 0; i < ATT_DN / 2; i++) r += acc0[i] + acc1[i];
    if (r == 123.456f) g_oA[0] = __float2bfloat16(r);
    if ((threadIdx.x & 127) == 0 && warp == 4 * (NWG + (ATT_X4 ? 0 : 1))) { g_dummy_cnt[blockIdx.x * 2] = n; g_dummy_cnt[blockIdx.x * 2 + 1] = t1 - t0; }
  } else if (role == 0) {
    reg_dealloc<ATT_PREGS>();
    if ((ATT_X4 || warp == 0) && lane == 0) {
      prefetch_tmap(&tm_kv);
      int stage = 0; uint32_t phase = 1;
      for (int item = blockIdx.x; item < A_ITEMS; item += gridDim.x) {
        const int h = item / (SEQ / A_ROWS);
        for (int j = 0; j < A_NSTG; j++) {
          mbar_wait(bar_empty + 8 * stage, phase);
          const uint32_t full = bar_full + 8 * stage, dst = sb + stage * A_STAGE_BYTES;
          mbar_expect_tx(full, A_STAGE_BYTES);
          tma_load_2d(dst, &tm_kv, full, 0, (NH + h) * SEQ + j * 128);
          tma_load_2d(dst + 8192, &tm_kv, full, 0, (2 * NH + h) * SEQ + j * 128);
          if (++stage == A_STAGES) { stage = 0; phase ^= 1; }
        }
      }
    }
  } else {
    if constexpr (ATT_CREGS >= ATT_LAUNCH_REGS) reg_alloc<ATT_CREGS>(); else reg_dealloc<ATT_CREGS>();
    const int wg = (warp >> 2) - (ATT_X4 ? 0 : 1), wq = warp & 3, tid = threadIdx.x & 127;
    const int qd = lane & 3, r8 = lane >> 2;
    const uint32_t ones = sb + A_ONES_OFF;
    int stage = 0; uint32_t phase = 0;
    if (ATT_PP && DBUF == 0 && wg == NWG - 1) named_bar_arrive(4, 256);
    for (int item = blockIdx.x; item < A_ITEMS; item += gridDim.x) {
      const int h = item / (SEQ / A_ROWS);
      const int row0 = (item % (SEQ / A_ROWS)) * A_ROWS + wg * 64;
      uint32_t q[8];
      {
        const uint32_t* qp = reinterpret_cast<const uint32_t*>(g_qkv + ((size_t)h * SEQ + row0 + wq * 16 + r8) * 32) + qd;
#pragma unroll
        for (int ks = 0; ks < 2; ks++) {
          q[4 * ks + 0] = __ldg(qp + ks * 8);
          q[4 * ks + 1] = __ldg(qp + ks * 8 + 8 * 16);
          q[4 * ks + 2] = __ldg(qp + ks * 8 + 4);
          q[4 * ks + 3] = __ldg(qp + ks * 8 + 4 + 8 * 16);
        }
      }
      bool fast;
      {
        const float4 kq = __ldg(reinterpret_cast<const float4*>(g_stats + (NH + h) * 128) + lane);
        const float4 vq = __ldg(reinterpret_cast<const float4*>(g_stats + (2 * NH + h) * 128) + lane);
        const float4 qq = __ldg(reinterpret_cast<const float4*>(g_stats + h * 128 + (row0 >> 4)));
        float km = fmaxf(fmaxf(kq.x, kq.y), fmaxf(kq.z, kq.w));
        float ks = (kq.x + kq.y) + (kq.z + kq.w);
        float vs = (vq.x + vq.y) + (vq.z + vq.w);
#pragma unroll
        for (int o = 1; o < 32; o <<= 1) {
          km = fmaxf(km, __shfl_xor_sync(0xffffffffu, km, o));
          ks += __shfl_xor_sync(0xffffffffu, ks, o);
          vs += __shfl_xor_sync(0xffffffffu, vs, o);
        }
        const float qm = fmaxf(fmaxf(qq.x, qq.y), fmaxf(qq.z, qq.w));
        const float qs = (qq.x + qq.y) + (qq.z + qq.w);
        fast = __all_sync(0xffffffffu, (qm * km <= 4000.f) && (ks <= 3.0e38f) && (qs <= 3.0e38f) && (vs <= 1.2e24f) && (vs >= 6.0e-14f));
      }
      float o[20];
#pragma unroll
      for (int i = 0; i < 20; i++) o[i] = 0.f;
      uint32_t p[BN / 4];

      if (fast) {
        if constexpr (DBUF == 0) {
          float s[BN / 2];
          mbar_wait(bar_full + 8 * stage, phase);
          uint32_t cur = sb + stage * A_STAGE_BYTES;
          int cst = stage;
          pp_sync<NWG>(wg);
          wg_fence();
          QKmma<BN>::run(s, q, desc_lo(cur, 16));
          wg_commit();
          pp_arrive<NWG>(wg);
          wg_wait<0>();
          fence_regs(s);
          exp_inplace<BN>(s);
          pack_p<BN>(p, s);
#pragma unroll 1
          for (int j = 0; j < NBLK - 1; j++) {
            uint32_t nxt; int nst = cst;
            const bool newstage = (BPS == 1) || ((j + 1) % BPS == 0);
            if (newstage) {
              if (++stage == A_STAGES) { stage = 0; phase ^= 1; }
              mbar_wait(bar_full + 8 * stage, phase);
              nxt = sb + stage * A_STAGE_BYTES; nst = stage;
            } else {
              nxt = cur + BN * 64;
            }
            pp_sync<NWG>(wg);
            wg_fence();
            QKmma<BN>::run(s, q, desc_lo(nxt, 16));
            wg_commit();
            pv_mma<BN>(o, p, cur + 8192, ones);
            wg_commit();
            pp_arrive<NWG>(wg);
            wg_wait<1>();
            fence_regs(s);
            exp_inplace<BN>(s);
            fence_regs(s);
            wg_wait<0>();
            if (newstage && tid == 0) mbar_arrive(bar_empty + 8 * cst);
            pack_p<BN>(p, s);
            cur = nxt; cst = nst;
          }
          wg_fence();
          pv_mma<BN>(o, p, cur + 8192, ones);
          wg_commit();
          wg_wait<0>();
          if (tid == 0) mbar_arrive(bar_empty + 8 * cst);
          if (++stage == A_STAGES) { stage = 0; phase ^= 1; }
        } else {
          float s0[BN / 2], s1[BN / 2];
          mbar_wait(bar_full + 8 * stage, phase);
          uint32_t cur = sb + stage * A_STAGE_BYTES; int cst = stage;
          uint32_t prv = 0; int pst = -1;
          wg_fence();
          QKmma<BN>::run(s0, q, desc_lo(cur, 16));
          wg_commit();
          auto step = [&](float (&sc)[BN / 2], float (&sn)[BN / 2], int j, bool last, bool first) {
            uint32_t nxt = cur; int nst = cst;
            if (!last) {
              if ((BPS == 1) || ((j + 1) % BPS == 0)) {
                if (++stage == A_STAGES) { stage = 0; phase ^= 1; }
                mbar_wait(bar_full + 8 * stage, phase);
                nxt = sb + stage * A_STAGE_BYTES; nst = stage;
              } else {
                nxt = cur + BN * 64;
              }
              wg_fence();
              QKmma<BN>::run(sn, q, desc_lo(nxt, 16));
              wg_commit();
              if (first) wg_wait<1>(); else wg_wait<2>();
            } else {
              wg_wait<1>();
            }
            if (DBUF == 1) {
              fence_regs(sc);
              exp_inplace<BN>(sc);
              fence_regs(sc);
              if (!first) {
                if (last) wg_wait<0>(); else wg_wait<1>();
                if (pst != cst && tid == 0) mbar_arrive(bar_empty + 8 * pst);
              }
              pack_p<BN>(p, sc);
              wg_fence();
              pv_mma<BN>(o, p, cur + 8192, ones);
              wg_commit();
            } else {
              fence_regs(sc);
              exp_pack<BN, 0, BN / 4>(p, sc);
              wg_fence();
              pv_mma<BN, 0, BN / 32>(o, p, cur + 8192, ones);
              wg_commit();
              if (!first) {
                if (last) wg_wait<1>(); else wg_wait<2>();
                if (pst != cst && tid == 0) mbar_arrive(bar_empty + 8 * pst);
              }
              exp_pack<BN, BN / 4, BN / 2>(p, sc);
              wg_fence();
              pv_mma<BN, BN / 32, BN / 16>(o, p, cur + 8192, ones);
              wg_commit();
            }
            prv = cur; pst = cst; cur = nxt; cst = nst;
          };
          step(s0, s1, 0, false, true);
#pragma unroll 1
          for (int j = 1; j < NBLK - 1; j += 2) {
            step(s1, s0, j, false, false);
            step(s0, s1, j + 1, false, false);
          }
          step(s1, s0, NBLK - 1, true, false);
          (void)prv;
          wg_wait<0>();
          if (tid == 0) mbar_arrive(bar_empty + 8 * pst);
          if (++stage == A_STAGES) { stage = 0; phase ^= 1; }
        }
      } else {
        float s[BN / 2];
        float m0 = -INFINITY, m1 = -INFINITY;
        uint32_t cur = 0;
#pragma unroll 1
        for (int j = 0; j < NBLK; j++) {
          if (j % BPS == 0) {
            mbar_wait(bar_full + 8 * stage, phase);
            cur = sb + stage * A_STAGE_BYTES;
          } else {
            cur += BN * 64;
          }
          if (DBUF == 0) pp_sync<NWG>(wg);
          wg_fence();
          QKmma<BN>::run(s, q, desc_lo(cur, 16));
          wg_commit();
          if (DBUF == 0) pp_arrive<NWG>(wg);
          wg_wait<0>();
          fence_regs(s);
          float n0 = m0, n1 = m1;
#pragma unroll
          for (int i = 0; i < BN / 8; i++) {
            n0 = fmaxf(n0, fmaxf(s[4 * i], s[4 * i + 1]));
            n1 = fmaxf(n1, fmaxf(s[4 * i + 2], s[4 * i + 3]));
          }
          n0 = fmaxf(n0, __shfl_xor_sync(0xffffffffu, n0, 1));
          n1 = fmaxf(n1, __shfl_xor_sync(0xffffffffu, n1, 1));
          n0 = fmaxf(n0, __shfl_xor_sync(0xffffffffu, n0, 2));
          n1 = fmaxf(n1, __shfl_xor_sync(0xffffffffu, n1, 2));
          const float c0 = exp2f(m0 - n0), c1 = exp2f(m1 - n1);
          m0 = n0; m1 = n1;
#pragma unroll
          for (int i = 0; i < 5; i++) {
            o[4 * i] *= c0; o[4 * i + 1] *= c0; o[4 * i + 2] *= c1; o[4 * i + 3] *= c1;
          }
#pragma unroll
          for (int i = 0; i < BN / 8; i++) {
            s[4 * i] = ex2_approx(s[4 * i] - m0); s[4 * i + 1] = ex2_approx(s[4 * i + 1] - m0);
            s[4 * i + 2] = ex2_approx(s[4 * i + 2] - m1); s[4 * i + 3] = ex2_approx(s[4 * i + 3] - m1);
          }
          pack_p<BN>(p, s);
          wg_fence();
          pv_mma<BN>(o, p, cur + 8192, ones);
          wg_commit();
          wg_wait<0>();
          fence_regs(o);
          if ((j + 1) % BPS == 0) {
            if (tid == 0) mbar_arrive(bar_empty + 8 * stage);
            if (++stage == A_STAGES) { stage = 0; phase ^= 1; }
          }
        }
      }
      fence_regs(o);
      const float i0 = 1.f / o[16], i1 = 1.f / o[18];
      uint32_t* op = reinterpret_cast<uint32_t*>(g_oA + (size_t)(row0 + wq * 16 + r8) * DM + h * 32) + qd;
#pragma unroll
      for (int j = 0; j < 4; j++) {
        op[4 * j] = pack_bf16(o[4 * j] * i0, o[4 * j + 1] * i0);
        op[4 * j + 8 * (DM / 2)] = pack_bf16(o[4 * j + 2] * i1, o[4 * j + 3] * i1);
      }
    }
    if (ATT_DUMMY && tid == 0) atomicAdd((int*)&s_done, 1);
  }
}

__device__ __forceinline__ void mma_bf16_16816(float (&d)[4], uint32_t a0, uint32_t a1, uint32_t a2, uint32_t a3, uint32_t b0, uint32_t b1) {
  asm volatile("mma.sync.aligned.m16n8k16.row.col.f32.bf16.bf16.f32 {%0,%1,%2,%3}, {%4,%5,%6,%7}, {%8,%9}, {%0,%1,%2,%3};"
               : "+f"(d[0]), "+f"(d[1]), "+f"(d[2]), "+f"(d[3]) : "r"(a0), "r"(a1), "r"(a2), "r"(a3), "r"(b0), "r"(b1));
}

__device__ __forceinline__ void linattn_job(int head, int blk0, int nblk, int lane) {
  const int qd = lane & 3, r8 = lane >> 2;
  uint32_t b[2][5][2];
  const float* kv = g_kv + head * 32 * 40;
#pragma unroll
  for (int ks = 0; ks < 2; ks++)
#pragma unroll
    for (int n = 0; n < 5; n++) {
      const float* c = kv + (ks * 16 + 2 * qd) * 40 + n * 8 + r8;
      b[ks][n][0] = pack_bf16(__ldcg(c), __ldcg(c + 40));
      b[ks][n][1] = pack_bf16(__ldcg(c + 8 * 40), __ldcg(c + 9 * 40));
    }
  for (int blk = blk0; blk < blk0 + nblk; blk++) {
    const uint32_t* ap = reinterpret_cast<const uint32_t*>(g_pq + (size_t)(blk * 16 + r8) * DM + head * 32) + qd;
    uint32_t a[8];
#pragma unroll
    for (int ks = 0; ks < 2; ks++) {
      a[4 * ks + 0] = __ldcg(ap + ks * 8);
      a[4 * ks + 1] = __ldcg(ap + ks * 8 + 8 * (DM / 2));
      a[4 * ks + 2] = __ldcg(ap + ks * 8 + 4);
      a[4 * ks + 3] = __ldcg(ap + ks * 8 + 4 + 8 * (DM / 2));
    }
    float d[5][4];
#pragma unroll
    for (int n = 0; n < 5; n++) {
      d[n][0] = d[n][1] = d[n][2] = d[n][3] = 0.f;
      mma_bf16_16816(d[n], a[0], a[1], a[2], a[3], b[0][n][0], b[0][n][1]);
      mma_bf16_16816(d[n], a[4], a[5], a[6], a[7], b[1][n][0], b[1][n][1]);
    }
    const float i0 = 1.f / (d[4][0] + 1e-6f), i1 = 1.f / (d[4][2] + 1e-6f);
    uint32_t* op = reinterpret_cast<uint32_t*>(g_oB + (size_t)(blk * 16 + r8) * DM + head * 32) + qd;
#pragma unroll
    for (int j = 0; j < 4; j++) {
      op[4 * j] = pack_bf16(d[j][0] * i0, d[j][1] * i0);
      op[4 * j + 8 * (DM / 2)] = pack_bf16(d[j][2] * i1, d[j][3] * i1);
    }
  }
}

__global__ void __launch_bounds__(128) linattn_kernel() {
  const int w = blockIdx.x * 4 + (threadIdx.x >> 5);
  linattn_job(w >> 4, (w & 15) * 8, 8, threadIdx.x & 31);
}

typedef CUresult (*PFN_encodeTiled)(CUtensorMap*, CUtensorMapDataType, cuuint32_t, void*, const cuuint64_t*, const cuuint64_t*,
                                    const cuuint32_t*, const cuuint32_t*, CUtensorMapInterleave, CUtensorMapSwizzle,
                                    CUtensorMapL2promotion, CUtensorMapFloatOOBfill);

static PFN_encodeTiled get_encode() {
  static PFN_encodeTiled fn = nullptr;
  if (!fn) {
    void* p = nullptr;
    cudaDriverEntryPointQueryResult q;
    cudaGetDriverEntryPoint("cuTensorMapEncodeTiled", &p, cudaEnableDefault, &q);
    fn = (PFN_encodeTiled)p;
  }
  return fn;
}

static void make_map(CUtensorMap* m, const void* base, int rank, const cuuint64_t* dims, const cuuint64_t* strides,
                     const cuuint32_t* box, CUtensorMapSwizzle swz) {
  cuuint32_t es[3] = {1, 1, 1};
  get_encode()(m, CU_TENSOR_MAP_DATA_TYPE_BFLOAT16, rank, const_cast<void*>(base), dims, strides, box, es,
               CU_TENSOR_MAP_INTERLEAVE_NONE, swz, CU_TENSOR_MAP_L2_PROMOTION_L2_256B, CU_TENSOR_MAP_FLOAT_OOB_FILL_NONE);
}
static void map_2d(CUtensorMap* m, const void* base, int rows, int cols, int bc, int br, CUtensorMapSwizzle swz) {
  cuuint64_t dims[2] = {(cuuint64_t)cols, (cuuint64_t)rows};
  cuuint64_t strides[1] = {(cuuint64_t)cols * 2};
  cuuint32_t box[2] = {(cuuint32_t)bc, (cuuint32_t)br};
  make_map(m, base, 2, dims, strides, box, swz);
}
static void map_w(CUtensorMap* m, const void* base, int K, int N) {
  cuuint64_t dims[3] = {64, (cuuint64_t)K, (cuuint64_t)(N / 64)};
  cuuint64_t strides[2] = {(cuuint64_t)N * 2, 128};
  cuuint32_t box[3] = {64, (cuuint32_t)G_BK, 2};
  make_map(m, base, 3, dims, strides, box, CU_TENSOR_MAP_SWIZZLE_128B);
}

struct Plan {
  GemmMaps m1, m3;
  CUtensorMap kv;
};

static void build_plan(Plan& P, void* const* d_in, void* d_out) {
  void *qkv, *oA, *oB, *pq;
  cudaGetSymbolAddress(&qkv, g_qkv); cudaGetSymbolAddress(&oA, g_oA);
  cudaGetSymbolAddress(&oB, g_oB); cudaGetSymbolAddress(&pq, g_pq);
  map_2d(&P.m1.a[0], d_in[0], SEQ, DM, G_BK, 128, CU_TENSOR_MAP_SWIZZLE_64B);
  map_2d(&P.m1.a[1], d_in[3], SEQ, DM, G_BK, 128, CU_TENSOR_MAP_SWIZZLE_64B);
  map_w(&P.m1.w[0], d_in[1], DM, 3 * DM);
  map_w(&P.m1.w[1], d_in[4], DM, 3 * DM);
  map_2d(&P.m1.st_head, qkv, 3 * NH * SEQ, 32, 32, 64, CU_TENSOR_MAP_SWIZZLE_64B);
  map_2d(&P.m1.st_row, pq, SEQ, DM, 64, 64, CU_TENSOR_MAP_SWIZZLE_128B);
  map_2d(&P.m3.a[0], oA, SEQ, DM, G_BK, 128, CU_TENSOR_MAP_SWIZZLE_64B);
  map_2d(&P.m3.a[1], oB, SEQ, DM, G_BK, 128, CU_TENSOR_MAP_SWIZZLE_64B);
  map_w(&P.m3.w[0], d_in[2], DM, DM);
  map_w(&P.m3.w[1], d_in[5], DM, DM);
  P.m3.st_head = P.m1.st_head;
  map_2d(&P.m3.st_row, d_out, SEQ, 2 * DM, 64, 64, CU_TENSOR_MAP_SWIZZLE_128B);
  map_2d(&P.kv, qkv, 3 * NH * SEQ, 32, 32, 128, CU_TENSOR_MAP_SWIZZLE_64B);
}

static void launch_k1(const Plan& P, cudaStream_t st) { gemm_kernel<0><<<132, 384, G_SMEM, st>>>(P.m1); }
static void launch_k2(const Plan& P, cudaStream_t st) {
  attn_kernel<ATT_NWG, ATT_BN, ATT_DBUF><<<132, ATT_THREADS, A_SMEM, st>>>(P.kv);
}
static void launch_k2b(const Plan& P, cudaStream_t st) { linattn_kernel<<<128, 128, 0, st>>>(); }
static void launch_k3(const Plan& P, cudaStream_t st) { gemm_kernel<1><<<128, 384, G_SMEM, st>>>(P.m3); }

static void set_attrs() {
  static bool done = false;
  if (done) return;
  done = true;
  cudaFuncSetAttribute(gemm_kernel<0>, cudaFuncAttributeMaxDynamicSharedMemorySize, G_SMEM);
  cudaFuncSetAttribute(gemm_kernel<1>, cudaFuncAttributeMaxDynamicSharedMemorySize, G_SMEM);
  cudaFuncSetAttribute(attn_kernel<ATT_NWG, ATT_BN, ATT_DBUF>, cudaFuncAttributeMaxDynamicSharedMemorySize, A_SMEM);
}

extern "C" void kernel_launch(void* const* d_in, const int* in_sizes, int n_in, void* d_out, int out_size) {
  set_attrs();
  Plan P;
  build_plan(P, d_in, d_out);
  cudaStream_t st = cudaStreamPerThread;
  launch_k1(P, st);
  launch_k2(P, st);
  launch_k2b(P, st);
  launch_k3(P, st);
}
```

```cpp
template <uint32_t HA, uint32_t HB>
__device__ __forceinline__ void wgmma_ss_n192_tb(float (&d)[96], uint32_t la, uint32_t lb) {
  asm volatile("{\n.reg .pred p;\n.reg .b64 da, db;\n"
    "mov.b64 da, {%96, %98};\nmov.b64 db, {%97, %99};\n"
    "setp.ne.b32 p, 1, 0;\n"
    "wgmma.mma_async.sync.aligned.m64n192k16.f32.bf16.bf16 "
    "{%0, %1, %2, %3, %4, %5, %6, %7, %8, %9, %10, %11, %12, %13, %14, %15, "
    "%16, %17, %18, %19, %20, %21, %22, %23, %24, %25, %26, %27, %28, %29, %30, %31, "
    "%32, %33, %34, %35, %36, %37, %38, %39, %40, %41, %42, %43, %44, %45, %46, %47, "
    "%48, %49, %50, %51, %52, %53, %54, %55, %56, %57, %58, %59, %60, %61, %62, %63, "
    "%64, %65, %66, %67, %68, %69, %70, %71, %72, %73, %74, %75, %76, %77, %78, %79, "
    "%80, %81, %82, %83, %84, %85, %86, %87, %88, %89, %90, %91, %92, %93, %94, %95}, "
    "da, db, p, 1, 1, 0, 1;\n}\n"
    : "+f"(d[0]), "+f"(d[1]), "+f"(d[2]), "+f"(d[3]), "+f"(d[4]), "+f"(d[5]), "+f"(d[6]), "+f"(d[7]),
      "+f"(d[8]), "+f"(d[9]), "+f"(d[10]), "+f"(d[11]), "+f"(d[12]), "+f"(d[13]), "+f"(d[14]), "+f"(d[15]),
      "+f"(d[16]), "+f"(d[17]), "+f"(d[18]), "+f"(d[19]), "+f"(d[20]), "+f"(d[21]), "+f"(d[22]), "+f"(d[23]),
      "+f"(d[24]), "+f"(d[25]), "+f"(d[26]), "+f"(d[27]), "+f"(d[28]), "+f"(d[29]), "+f"(d[30]), "+f"(d[31]),
      "+f"(d[32]), "+f"(d[33]), "+f"(d[34]), "+f"(d[35]), "+f"(d[36]), "+f"(d[37]), "+f"(d[38]), "+f"(d[39]),
      "+f"(d[40]), "+f"(d[41]), "+f"(d[42]), "+f"(d[43]), "+f"(d[44]), "+f"(d[45]), "+f"(d[46]), "+f"(d[47]),
      "+f"(d[48]), "+f"(d[49]), "+f"(d[50]), "+f"(d[51]), "+f"(d[52]), "+f"(d[53]), "+f"(d[54]), "+f"(d[55]),
      "+f"(d[56]), "+f"(d[57]), "+f"(d[58]), "+f"(d[59]), "+f"(d[60]), "+f"(d[61]), "+f"(d[62]), "+f"(d[63]),
      "+f"(d[64]), "+f"(d[65]), "+f"(d[66]), "+f"(d[67]), "+f"(d[68]), "+f"(d[69]), "+f"(d[70]), "+f"(d[71]),
      "+f"(d[72]), "+f"(d[73]), "+f"(d[74]), "+f"(d[75]), "+f"(d[76]), "+f"(d[77]), "+f"(d[78]), "+f"(d[79]),
      "+f"(d[80]), "+f"(d[81]), "+f"(d[82]), "+f"(d[83]), "+f"(d[84]), "+f"(d[85]), "+f"(d[86]), "+f"(d[87]),
      "+f"(d[88]), "+f"(d[89]), "+f"(d[90]), "+f"(d[91]), "+f"(d[92]), "+f"(d[93]), "+f"(d[94]), "+f"(d[95])
    : "r"(la), "r"(lb), "n"(HA), "n"(HB));
}
template <uint32_t HA, uint32_t HB>
__device__ __forceinline__ void wgmma_ss_n192_tb_z(float (&d)[96], uint32_t la, uint32_t lb) {
  asm volatile("{\n.reg .pred p;\n.reg .b64 da, db;\n"
    "mov.b64 da, {%96, %98};\nmov.b64 db, {%97, %99};\n"
    "setp.ne.b32 p, 0, 0;\n"
    "wgmma.mma_async.sync.aligned.m64n192k16.f32.bf16.bf16 "
    "{%0, %1, %2, %3, %4, %5, %6, %7, %8, %9, %10, %11, %12, %13, %14, %15, "
    "%16, %17, %18, %19, %20, %21, %22, %23, %24, %25, %26, %27, %28, %29, %30, %31, "
    "%32, %33, %34, %35, %36, %37, %38, %39, %40, %41, %42, %43, %44, %45, %46, %47, "
    "%48, %49, %50, %51, %52, %53, %54, %55, %56, %57, %58, %59, %60, %61, %62, %63, "
    "%64, %65, %66, %67, %68, %69, %70, %71, %72, %73, %74, %75, %76, %77, %78, %79, "
    "%80, %81, %82, %83, %84, %85, %86, %87, %88, %89, %90, %91, %92, %93, %94, %95}, "
    "da, db, p, 1, 1, 0, 1;\n}\n"
    : "=f"(d[0]), "=f"(d[1]), "=f"(d[2]), "=f"(d[3]), "=f"(d[4]), "=f"(d[5]), "=f"(d[6]), "=f"(d[7]),
      "=f"(d[8]), "=f"(d[9]), "=f"(d[10]), "=f"(d[11]), "=f"(d[12]), "=f"(d[13]), "=f"(d[14]), "=f"(d[15]),
      "=f"(d[16]), "=f"(d[17]), "=f"(d[18]), "=f"(d[19]), "=f"(d[20]), "=f"(d[21]), "=f"(d[22]), "=f"(d[23]),
      "=f"(d[24]), "=f"(d[25]), "=f"(d[26]), "=f"(d[27]), "=f"(d[28]), "=f"(d[29]), "=f"(d[30]), "=f"(d[31]),
      "=f"(d[32]), "=f"(d[33]), "=f"(d[34]), "=f"(d[35]), "=f"(d[36]), "=f"(d[37]), "=f"(d[38]), "=f"(d[39]),
      "=f"(d[40]), "=f"(d[41]), "=f"(d[42]), "=f"(d[43]), "=f"(d[44]), "=f"(d[45]), "=f"(d[46]), "=f"(d[47]),
      "=f"(d[48]), "=f"(d[49]), "=f"(d[50]), "=f"(d[51]), "=f"(d[52]), "=f"(d[53]), "=f"(d[54]), "=f"(d[55]),
      "=f"(d[56]), "=f"(d[57]), "=f"(d[58]), "=f"(d[59]), "=f"(d[60]), "=f"(d[61]), "=f"(d[62]), "=f"(d[63]),
      "=f"(d[64]), "=f"(d[65]), "=f"(d[66]), "=f"(d[67]), "=f"(d[68]), "=f"(d[69]), "=f"(d[70]), "=f"(d[71]),
      "=f"(d[72]), "=f"(d[73]), "=f"(d[74]), "=f"(d[75]), "=f"(d[76]), "=f"(d[77]), "=f"(d[78]), "=f"(d[79]),
      "=f"(d[80]), "=f"(d[81]), "=f"(d[82]), "=f"(d[83]), "=f"(d[84]), "=f"(d[85]), "=f"(d[86]), "=f"(d[87]),
      "=f"(d[88]), "=f"(d[89]), "=f"(d[90]), "=f"(d[91]), "=f"(d[92]), "=f"(d[93]), "=f"(d[94]), "=f"(d[95])
    : "r"(la), "r"(lb), "n"(HA), "n"(HB));
}
template <uint32_t HA, uint32_t HB>
__device__ __forceinline__ void wgmma_ss_n128_tb(float (&d)[64], uint32_t la, uint32_t lb) {
  asm volatile("{\n.reg .pred p;\n.reg .b64 da, db;\n"
    "mov.b64 da, {%64, %66};\nmov.b64 db, {%65, %67};\n"
    "setp.ne.b32 p, 1, 0;\n"
    "wgmma.mma_async.sync.aligned.m64n128k16.f32.bf16.bf16 "
    "{%0, %1, %2, %3, %4, %5, %6, %7, %8, %9, %10, %11, %12, %13, %14, %15, "
    "%16, %17, %18, %19, %20, %21, %22, %23, %24, %25, %26, %27, %28, %29, %30, %31, "
    "%32, %33, %34, %35, %36, %37, %38, %39, %40, %41, %42, %43, %44, %45, %46, %47, "
    "%48, %49, %50, %51, %52, %53, %54, %55, %56, %57, %58, %59, %60, %61, %62, %63}, "
    "da, db, p, 1, 1, 0, 1;\n}\n"
    : "+f"(d[0]), "+f"(d[1]), "+f"(d[2]), "+f"(d[3]), "+f"(d[4]), "+f"(d[5]), "+f"(d[6]), "+f"(d[7]),
      "+f"(d[8]), "+f"(d[9]), "+f"(d[10]), "+f"(d[11]), "+f"(d[12]), "+f"(d[13]), "+f"(d[14]), "+f"(d[15]),
      "+f"(d[16]), "+f"(d[17]), "+f"(d[18]), "+f"(d[19]), "+f"(d[20]), "+f"(d[21]), "+f"(d[22]), "+f"(d[23]),
      "+f"(d[24]), "+f"(d[25]), "+f"(d[26]), "+f"(d[27]), "+f"(d[28]), "+f"(d[29]), "+f"(d[30]), "+f"(d[31]),
      "+f"(d[32]), "+f"(d[33]), "+f"(d[34]), "+f"(d[35]), "+f"(d[36]), "+f"(d[37]), "+f"(d[38]), "+f"(d[39]),
      "+f"(d[40]), "+f"(d[41]), "+f"(d[42]), "+f"(d[43]), "+f"(d[44]), "+f"(d[45]), "+f"(d[46]), "+f"(d[47]),
      "+f"(d[48]), "+f"(d[49]), "+f"(d[50]), "+f"(d[51]), "+f"(d[52]), "+f"(d[53]), "+f"(d[54]), "+f"(d[55]),
      "+f"(d[56]), "+f"(d[57]), "+f"(d[58]), "+f"(d[59]), "+f"(d[60]), "+f"(d[61]), "+f"(d[62]), "+f"(d[63])
    : "r"(la), "r"(lb), "n"(HA), "n"(HB));
}
template <uint32_t HA, uint32_t HB>
__device__ __forceinline__ void wgmma_ss_n128_tb_z(float (&d)[64], uint32_t la, uint32_t lb) {
  asm volatile("{\n.reg .pred p;\n.reg .b64 da, db;\n"
    "mov.b64 da, {%64, %66};\nmov.b64 db, {%65, %67};\n"
    "setp.ne.b32 p, 0, 0;\n"
    "wgmma.mma_async.sync.aligned.m64n128k16.f32.bf16.bf16 "
    "{%0, %1, %2, %3, %4, %5, %6, %7, %8, %9, %10, %11, %12, %13, %14, %15, "
    "%16, %17, %18, %19, %20, %21, %22, %23, %24, %25, %26, %27, %28, %29, %30, %31, "
    "%32, %33, %34, %35, %36, %37, %38, %39, %40, %41, %42, %43, %44, %45, %46, %47, "
    "%48, %49, %50, %51, %52, %53, %54, %55, %56, %57, %58, %59, %60, %61, %62, %63}, "
    "da, db, p, 1, 1, 0, 1;\n}\n"
    : "=f"(d[0]), "=f"(d[1]), "=f"(d[2]), "=f"(d[3]), "=f"(d[4]), "=f"(d[5]), "=f"(d[6]), "=f"(d[7]),
      "=f"(d[8]), "=f"(d[9]), "=f"(d[10]), "=f"(d[11]), "=f"(d[12]), "=f"(d[13]), "=f"(d[14]), "=f"(d[15]),
      "=f"(d[16]), "=f"(d[17]), "=f"(d[18]), "=f"(d[19]), "=f"(d[20]), "=f"(d[21]), "=f"(d[22]), "=f"(d[23]),
      "=f"(d[24]), "=f"(d[25]), "=f"(d[26]), "=f"(d[27]), "=f"(d[28]), "=f"(d[29]), "=f"(d[30]), "=f"(d[31]),
      "=f"(d[32]), "=f"(d[33]), "=f"(d[34]), "=f"(d[35]), "=f"(d[36]), "=f"(d[37]), "=f"(d[38]), "=f"(d[39]),
      "=f"(d[40]), "=f"(d[41]), "=f"(d[42]), "=f"(d[43]), "=f"(d[44]), "=f"(d[45]), "=f"(d[46]), "=f"(d[47]),
      "=f"(d[48]), "=f"(d[49]), "=f"(d[50]), "=f"(d[51]), "=f"(d[52]), "=f"(d[53]), "=f"(d[54]), "=f"(d[55]),
      "=f"(d[56]), "=f"(d[57]), "=f"(d[58]), "=f"(d[59]), "=f"(d[60]), "=f"(d[61]), "=f"(d[62]), "=f"(d[63])
    : "r"(la), "r"(lb), "n"(HA), "n"(HB));
}
template <uint32_t HA, uint32_t HB>
__device__ __forceinline__ void wgmma_ss_n40_tb_ta(float (&d)[20], uint32_t la, uint32_t lb) {
  asm volatile("{\n.reg .pred p;\n.reg .b64 da, db;\n"
    "mov.b64 da, {%20, %22};\nmov.b64 db, {%21, %23};\n"
    "setp.ne.b32 p, 1, 0;\n"
    "wgmma.mma_async.sync.aligned.m64n40k16.f32.bf16.bf16 "
    "{%0, %1, %2, %3, %4, %5, %6, %7, %8, %9, %10, %11, %12, %13, %14, %15, "
    "%16, %17, %18, %19}, "
    "da, db, p, 1, 1, 1, 1;\n}\n"
    : "+f"(d[0]), "+f"(d[1]), "+f"(d[2]), "+f"(d[3]), "+f"(d[4]), "+f"(d[5]), "+f"(d[6]), "+f"(d[7]),
      "+f"(d[8]), "+f"(d[9]), "+f"(d[10]), "+f"(d[11]), "+f"(d[12]), "+f"(d[13]), "+f"(d[14]), "+f"(d[15]),
      "+f"(d[16]), "+f"(d[17]), "+f"(d[18]), "+f"(d[19])
    : "r"(la), "r"(lb), "n"(HA), "n"(HB));
}
template <uint32_t HA, uint32_t HB>
__device__ __forceinline__ void wgmma_ss_n40_tb_ta_z(float (&d)[20], uint32_t la, uint32_t lb) {
  asm volatile("{\n.reg .pred p;\n.reg .b64 da, db;\n"
    "mov.b64 da, {%20, %22};\nmov.b64 db, {%21, %23};\n"
    "setp.ne.b32 p, 0, 0;\n"
    "wgmma.mma_async.sync.aligned.m64n40k16.f32.bf16.bf16 "
    "{%0, %1, %2, %3, %4, %5, %6, %7, %8, %9, %10, %11, %12, %13, %14, %15, "
    "%16, %17, %18, %19}, "
    "da, db, p, 1, 1, 1, 1;\n}\n"
    : "=f"(d[0]), "=f"(d[1]), "=f"(d[2]), "=f"(d[3]), "=f"(d[4]), "=f"(d[5]), "=f"(d[6]), "=f"(d[7]),
      "=f"(d[8]), "=f"(d[9]), "=f"(d[10]), "=f"(d[11]), "=f"(d[12]), "=f"(d[13]), "=f"(d[14]), "=f"(d[15]),
      "=f"(d[16]), "=f"(d[17]), "=f"(d[18]), "=f"(d[19])
    : "r"(la), "r"(lb), "n"(HA), "n"(HB));
}
template <uint32_t HB>
__device__ __forceinline__ void wgmma_rs_n40_tb(float (&d)[20], uint32_t a0, uint32_t a1, uint32_t a2, uint32_t a3, uint32_t lb) {
  asm volatile("{\n.reg .pred p;\n.reg .b64 db;\n"
    "mov.b64 db, {%24, %25};\n"
    "setp.ne.b32 p, 1, 0;\n"
    "wgmma.mma_async.sync.aligned.m64n40k16.f32.bf16.bf16 "
    "{%0, %1, %2, %3, %4, %5, %6, %7, %8, %9, %10, %11, %12, %13, %14, %15, "
    "%16, %17, %18, %19}, "
    "{%20, %21, %22, %23}, db, p, 1, 1, 1;\n}\n"
    : "+f"(d[0]), "+f"(d[1]), "+f"(d[2]), "+f"(d[3]), "+f"(d[4]), "+f"(d[5]), "+f"(d[6]), "+f"(d[7]),
      "+f"(d[8]), "+f"(d[9]), "+f"(d[10]), "+f"(d[11]), "+f"(d[12]), "+f"(d[13]), "+f"(d[14]), "+f"(d[15]),
      "+f"(d[16]), "+f"(d[17]), "+f"(d[18]), "+f"(d[19])
    : "r"(a0), "r"(a1), "r"(a2), "r"(a3), "r"(lb), "n"(HB));
}
template <uint32_t HB>
__device__ __forceinline__ void wgmma_rs_n40_tb_z(float (&d)[20], uint32_t a0, uint32_t a1, uint32_t a2, uint32_t a3, uint32_t lb) {
  asm volatile("{\n.reg .pred p;\n.reg .b64 db;\n"
    "mov.b64 db, {%24, %25};\n"
    "setp.ne.b32 p, 0, 0;\n"
    "wgmma.mma_async.sync.aligned.m64n40k16.f32.bf16.bf16 "
    "{%0, %1, %2, %3, %4, %5, %6, %7, %8, %9, %10, %11, %12, %13, %14, %15, "
    "%16, %17, %18, %19}, "
    "{%20, %21, %22, %23}, db, p, 1, 1, 1;\n}\n"
    : "=f"(d[0]), "=f"(d[1]), "=f"(d[2]), "=f"(d[3]), "=f"(d[4]), "=f"(d[5]), "=f"(d[6]), "=f"(d[7]),
      "=f"(d[8]), "=f"(d[9]), "=f"(d[10]), "=f"(d[11]), "=f"(d[12]), "=f"(d[13]), "=f"(d[14]), "=f"(d[15]),
      "=f"(d[16]), "=f"(d[17]), "=f"(d[18]), "=f"(d[19])
    : "r"(a0), "r"(a1), "r"(a2), "r"(a3), "r"(lb), "n"(HB));
}
template <uint32_t HB>
__device__ __forceinline__ void wgmma_rs_n32(float (&d)[16], uint32_t a0, uint32_t a1, uint32_t a2, uint32_t a3, uint32_t lb) {
  asm volatile("{\n.reg .pred p;\n.reg .b64 db;\n"
    "mov.b64 db, {%20, %21};\n"
    "setp.ne.b32 p, 1, 0;\n"
    "wgmma.mma_async.sync.aligned.m64n32k16.f32.bf16.bf16 "
    "{%0, %1, %2, %3, %4, %5, %6, %7, %8, %9, %10, %11, %12, %13, %14, %15}, "
    "{%16, %17, %18, %19}, db, p, 1, 1, 0;\n}\n"
    : "+f"(d[0]), "+f"(d[1]), "+f"(d[2]), "+f"(d[3]), "+f"(d[4]), "+f"(d[5]), "+f"(d[6]), "+f"(d[7]),
      "+f"(d[8]), "+f"(d[9]), "+f"(d[10]), "+f"(d[11]), "+f"(d[12]), "+f"(d[13]), "+f"(d[14]), "+f"(d[15])
    : "r"(a0), "r"(a1), "r"(a2), "r"(a3), "r"(lb), "n"(HB));
}
template <uint32_t HB>
__device__ __forceinline__ void wgmma_rs_n32_z(float (&d)[16], uint32_t a0, uint32_t a1, uint32_t a2, uint32_t a3, uint32_t lb) {
  asm volatile("{\n.reg .pred p;\n.reg .b64 db;\n"
    "mov.b64 db, {%20, %21};\n"
    "setp.ne.b32 p, 0, 0;\n"
    "wgmma.mma_async.sync.aligned.m64n32k16.f32.bf16.bf16 "
    "{%0, %1, %2, %3, %4, %5, %6, %7, %8, %9, %10, %11, %12, %13, %14, %15}, "
    "{%16, %17, %18, %19}, db, p, 1, 1, 0;\n}\n"
    : "=f"(d[0]), "=f"(d[1]), "=f"(d[2]), "=f"(d[3]), "=f"(d[4]), "=f"(d[5]), "=f"(d[6]), "=f"(d[7]),
      "=f"(d[8]), "=f"(d[9]), "=f"(d[10]), "=f"(d[11]), "=f"(d[12]), "=f"(d[13]), "=f"(d[14]), "=f"(d[15])
    : "r"(a0), "r"(a1), "r"(a2), "r"(a3), "r"(lb), "n"(HB));
}
template <uint32_t HB>
__device__ __forceinline__ void wgmma_rs_n64(float (&d)[32], uint32_t a0, uint32_t a1, uint32_t a2, uint32_t a3, uint32_t lb) {
  asm volatile("{\n.reg .pred p;\n.reg .b64 db;\n"
    "mov.b64 db, {%36, %37};\n"
    "setp.ne.b32 p, 1, 0;\n"
    "wgmma.mma_async.sync.aligned.m64n64k16.f32.bf16.bf16 "
    "{%0, %1, %2, %3, %4, %5, %6, %7, %8, %9, %10, %11, %12, %13, %14, %15, "
    "%16, %17, %18, %19, %20, %21, %22, %23, %24, %25, %26, %27, %28, %29, %30, %31}, "
    "{%32, %33, %34, %35}, db, p, 1, 1, 0;\n}\n"
    : "+f"(d[0]), "+f"(d[1]), "+f"(d[2]), "+f"(d[3]), "+f"(d[4]), "+f"(d[5]), "+f"(d[6]), "+f"(d[7]),
      "+f"(d[8]), "+f"(d[9]), "+f"(d[10]), "+f"(d[11]), "+f"(d[12]), "+f"(d[13]), "+f"(d[14]), "+f"(d[15]),
      "+f"(d[16]), "+f"(d[17]), "+f"(d[18]), "+f"(d[19]), "+f"(d[20]), "+f"(d[21]), "+f"(d[22]), "+f"(d[23]),
      "+f"(d[24]), "+f"(d[25]), "+f"(d[26]), "+f"(d[27]), "+f"(d[28]), "+f"(d[29]), "+f"(d[30]), "+f"(d[31])
    : "r"(a0), "r"(a1), "r"(a2), "r"(a3), "r"(lb), "n"(HB));
}
template <uint32_t HB>
__device__ __forceinline__ void wgmma_rs_n64_z(float (&d)[32], uint32_t a0, uint32_t a1, uint32_t a2, uint32_t a3, uint32_t lb) {
  asm volatile("{\n.reg .pred p;\n.reg .b64 db;\n"
    "mov.b64 db, {%36, %37};\n"
    "setp.ne.b32 p, 0, 0;\n"
    "wgmma.mma_async.sync.aligned.m64n64k16.f32.bf16.bf16 "
    "{%0, %1, %2, %3, %4, %5, %6, %7, %8, %9, %10, %11, %12, %13, %14, %15, "
    "%16, %17, %18, %19, %20, %21, %22, %23, %24, %25, %26, %27, %28, %29, %30, %31}, "
    "{%32, %33, %34, %35}, db, p, 1, 1, 0;\n}\n"
    : "=f"(d[0]), "=f"(d[1]), "=f"(d[2]), "=f"(d[3]), "=f"(d[4]), "=f"(d[5]), "=f"(d[6]), "=f"(d[7]),
      "=f"(d[8]), "=f"(d[9]), "=f"(d[10]), "=f"(d[11]), "=f"(d[12]), "=f"(d[13]), "=f"(d[14]), "=f"(d[15]),
      "=f"(d[16]), "=f"(d[17]), "=f"(d[18]), "=f"(d[19]), "=f"(d[20]), "=f"(d[21]), "=f"(d[22]), "=f"(d[23]),
      "=f"(d[24]), "=f"(d[25]), "=f"(d[26]), "=f"(d[27]), "=f"(d[28]), "=f"(d[29]), "=f"(d[30]), "=f"(d[31])
    : "r"(a0), "r"(a1), "r"(a2), "r"(a3), "r"(lb), "n"(HB));
}
#include <type_traits>

constexpr int SEQ = 2048, DM = 1024, NH = 32;
constexpr int NPAIR = 66;

constexpr float QSCALE = 0.17677669529663687f * 1.4426950408889634f;
constexpr float LOG2E = 1.4426950408889634f;

__device__ __align__(1024) uint8_t g_qkv[3 * NH * SEQ * 64];
__device__ __align__(1024) uint8_t g_o[2 * 16 * NH * 8192];
__device__ __align__(16) float g_stats[3 * NH * 128];
__device__ __align__(128) float g_kv[NH * 32 * 40];
__device__ __align__(128) uint32_t g_kvb[NH * 640];

enum { C_AKV = 0, C_ATT = 16, C_BKV = 32, C_KVB = 48, C_AQ = 64, C_BQ = 128, C_NUM = 136 };
__device__ uint32_t g_cnt[C_NUM * 8];
__device__ uint32_t g_epoch, g_exit;

enum { T_AKV = 0, T_AQ = 1, T_BKV = 2, T_BQ = 3, T_BOUT = 4, T_AOUT = 5, T_NONE = 7 };
constexpr int MAXT = 8;

struct MegaParams {
  CUtensorMap x[2];
  CUtensorMap wkv[2];
  CUtensorMap wblk[4];
  CUtensorMap out;
  const uint8_t* xa; const uint8_t* wa;
  uint16_t gt[NPAIR][MAXT];
  uint8_t at[NPAIR][4];
  uint8_t na[NPAIR];
};

constexpr int G_STAGES = 4;
constexpr int G_STAGE = 32768;
constexpr int S_STG = G_STAGES * G_STAGE;
constexpr int KV_STAGES = 3;
constexpr int S_KV = S_STG + 32768;
constexpr int S_OST = S_KV + KV_STAGES * 16384;
constexpr int S_ONES = S_OST + 8192;
constexpr int S_STAT = S_ONES + 1024;
constexpr int S_BAR = S_STAT + 192;
constexpr int G_STAGES0 = 6;
constexpr int B_GFULL = S_BAR, B_GEMPTY = B_GFULL + 8 * G_STAGES0;
constexpr int B_T0DONE = B_GEMPTY + 8 * G_STAGES0, B_LFREE = B_T0DONE + 8, B_ADONE = B_LFREE + 8;
constexpr int B_KFULL = B_ADONE + 8, B_KEMPTY = B_KFULL + 8 * KV_STAGES;
constexpr int B_SFULL = B_KEMPTY + 8 * KV_STAGES, B_SFREE = B_SFULL + 8;
constexpr int B_OFULL = B_SFREE + 8, B_OFREE = B_OFULL + 16;
constexpr int B_RDY = B_OFREE + 16, B_VERD = B_RDY + 8;
constexpr int S_FAST = B_VERD + 8;
constexpr int MEGA_SMEM = S_FAST + 32 + 1024;
static_assert(MEGA_SMEM <= 232448, "shared memory");

constexpr uint32_t HI_NOSW_128 = (128 >> 4);

#ifndef M_AREGS
#define M_AREGS 128
#endif
#ifndef M_GREGS
#define M_GREGS 184
#endif
#ifndef M_PREGS
#define M_PREGS 72
#endif
#ifndef M_GSPLIT
#define M_GSPLIT 0
#endif
#ifndef M_GWAIT
#define M_GWAIT 0
#endif

template <int I> using IC = std::integral_constant<int, I>;
template <int N, class F, int I = 0> __device__ __forceinline__ void static_for(F&& f) {
  if constexpr (I < N) { f(IC<I>{}); static_for<N, F, I + 1>(static_cast<F&&>(f)); }
}

#define TIMR(role, i)

__device__ __forceinline__ uint32_t ld_relaxed(const uint32_t* p) {
  uint32_t v;
  asm volatile("ld.relaxed.gpu.global.u32 %0, [%1];" : "=r"(v) : "l"(p) : "memory");
  return v;
}
__device__ __forceinline__ void fence_proxy_async_all() { asm volatile("fence.proxy.async;" ::: "memory"); }
#ifndef M_FENCE
#define M_FENCE 0
#endif
#ifndef M_SLEEP
#define M_SLEEP 40
#endif
__device__ __forceinline__ void cnt_wait(int c, uint32_t epoch, uint32_t target) {
  const uint32_t* p = g_cnt + c * 8;
  const uint32_t want = epoch * target + target;
  uint32_t spins = 0;
  while ((int32_t)(ld_relaxed(p) - want) < 0) {
    __nanosleep(M_SLEEP);
    if (++spins > (1u << 22)) __trap();
  }
  if (M_FENCE) { asm volatile("fence.acq_rel.gpu;" ::: "memory"); fence_proxy_async_all(); }
}
__device__ __forceinline__ void cnt_wait2(int c0, uint32_t t0, int c1, uint32_t t1, uint32_t epoch) {
  const uint32_t *p0 = g_cnt + c0 * 8, *p1 = g_cnt + c1 * 8;
  const uint32_t w0 = epoch * t0 + t0, w1 = epoch * t1 + t1;
  uint32_t spins = 0;
  while (true) {
    const uint32_t a = ld_relaxed(p0), b = ld_relaxed(p1);
    if ((int32_t)(a - w0) >= 0 && (int32_t)(b - w1) >= 0) break;
    __nanosleep(M_SLEEP);
    if (++spins > (1u << 22)) __trap();
  }
  if (M_FENCE) { asm volatile("fence.acq_rel.gpu;" ::: "memory"); fence_proxy_async_all(); }
}
__device__ __forceinline__ uint32_t cnt_add(int c) {
  uint32_t old;
  if (M_FENCE) { fence_proxy_async_all(); asm volatile("fence.acq_rel.gpu;" ::: "memory"); }
  asm volatile("atom.add.relaxed.gpu.global.u32 %0, [%1], 1;" : "=r"(old) : "l"(g_cnt + c * 8) : "memory");
  return old;
}
__device__ __forceinline__ void cnt_red(int c, uint32_t v) {
  if (M_FENCE) { fence_proxy_async_all(); asm volatile("fence.acq_rel.gpu;" ::: "memory"); }
  asm volatile("red.add.relaxed.gpu.global.u32 [%0], %1;" ::"l"(g_cnt + c * 8), "r"(v) : "memory");
}

struct Tile { int type, idx, mp; };
__device__ __forceinline__ Tile decode_tile(uint32_t e) { return Tile{(int)(e & 7), (int)((e >> 3) & 15), (int)(e >> 7)}; }

__device__ __forceinline__ float phi_fn(float t) {
  const float e = ex2_approx(t * LOG2E);
  const float y = t > 0.f ? t + 1.f : e;
  return y + 1e-6f;
}
__device__ __forceinline__ void bulk_load_1d(uint32_t dst, const void* src, uint32_t bytes, uint32_t bar) {
  asm volatile("cp.async.bulk.shared::cluster.global.mbarrier::complete_tx::bytes [%0], [%1], %2, [%3];"
               ::"r"(dst), "l"(src), "r"(bytes), "r"(bar) : "memory");
}
__device__ __forceinline__ void bulk_load_1d_mc(uint32_t dst, const void* src, uint32_t bytes, uint32_t bar, uint16_t mask) {
  asm volatile("cp.async.bulk.shared::cluster.global.mbarrier::complete_tx::bytes.multicast::cluster [%0], [%1], %2, [%3], %4;"
               ::"r"(dst), "l"(src), "r"(bytes), "r"(bar), "h"(mask) : "memory");
}
__device__ __forceinline__ void bulk_store_1d(void* dst, uint32_t src, uint32_t bytes) {
  asm volatile("cp.async.bulk.global.shared::cta.bulk_group [%0], [%1], %2;" ::"l"(dst), "r"(src), "r"(bytes) : "memory");
}
template <int N> struct Ring {
  int slot; uint32_t phase;
  __device__ __forceinline__ void advance() { if (++slot == N) { slot = 0; phase ^= 1; } }
  __device__ __forceinline__ Ring next() const { Ring r = *this; r.advance(); return r; }
};
__device__ __forceinline__ void bulk_reduce_add_f32(void* dst, uint32_t src, uint32_t bytes) {
  asm volatile("cp.reduce.async.bulk.global.shared::cta.bulk_group.add.f32 [%0], [%1], %2;" ::"l"(dst), "r"(src), "r"(bytes) : "memory");
}

#define KV_MC 1
#define ATT_SB 32
#define ATT_EARLY 4
__device__ __forceinline__ float ex2_volatile(float x) {
  float y;
  asm volatile("ex2.approx.ftz.f32 %0, %1;" : "=f"(y) : "f"(x));
  return y;
}
using KvRing = Ring<KV_STAGES>;
template <int SB> struct QKmma;
template <> struct QKmma<32> {
  static __device__ __forceinline__ void run(float (&s)[16], const uint32_t (&q)[8], uint32_t d) {
    wgmma_rs_n32_z<HI_SW64_512>(s, q[0], q[1], q[2], q[3], d);
    wgmma_rs_n32<HI_SW64_512>(s, q[4], q[5], q[6], q[7], d + 2);
  }
};
template <> struct QKmma<64> {
  static __device__ __forceinline__ void run(float (&s)[32], const uint32_t (&q)[8], uint32_t d) {
    wgmma_rs_n64_z<HI_SW64_512>(s, q[0], q[1], q[2], q[3], d);
    wgmma_rs_n64<HI_SW64_512>(s, q[4], q[5], q[6], q[7], d + 2);
  }
};
template <class Release, class Tail>
__device__ __forceinline__ void attn_item_fast(float (&o)[20], const uint32_t (&q)[8], uint32_t sb, KvRing& r, Release&& release, Tail&& tail_hook) {
  constexpr int SB = ATT_SB, U = 128 / SB, NP = SB / 4;
  constexpr uint32_t SOFF = SB * 4;
  float S[2][SB / 2];
  uint32_t P[2][NP];
  const uint32_t kd0 = desc_lo(sb + S_KV, 16), vd0 = desc_lo(sb + S_KV + 8192, (uint32_t)(S_ONES - S_KV - 8192));
  auto pv = [&](const uint32_t (&p)[NP], uint32_t vo) {
    const uint32_t d0 = vd0 + vo - (vo << 16);
#pragma unroll
    for (int k = 0; k < SB / 16; k++)
      wgmma_rs_n40_tb<HI_SW64_512>(o, p[4 * k], p[4 * k + 1], p[4 * k + 2], p[4 * k + 3], d0 + 64u * k - ((64u * k) << 16));
  };
  wg_fence();
  QKmma<SB>::run(S[0], q, kd0 + (uint32_t)r.slot * 1024u);
  wg_commit();
  wg_commit();
  int prev_slot = -1;
  auto step = [&](auto uc, auto issue_c, auto first_c, const KvRing& nx) {
    constexpr int u = decltype(uc)::value;
    constexpr bool issue = decltype(issue_c)::value, first = decltype(first_c)::value;
    const uint32_t a0 = (uint32_t)r.slot * 1024u;
    if constexpr (issue) {
      if constexpr (u == U - 1) mbar_wait(sb + B_KFULL + 8 * nx.slot, nx.phase);
      wg_fence();
      QKmma<SB>::run(S[(u + 1) & 1], q, kd0 + (u == U - 1 ? (uint32_t)nx.slot * 1024u : a0 + (u + 1) * SOFF));
    }
    wg_commit();
    wg_wait<1>();
    fence_regs(S[u & 1]);
    if constexpr (u == 1) { if (prev_slot >= 0) release(prev_slot); }
    float e[ATT_EARLY];
#pragma unroll
    for (int i = 0; i < ATT_EARLY; i++) e[i] = ex2_volatile(S[u & 1][i]);
    if constexpr (!first) {
      wg_fence();
      pv(P[(u + 1) & 1], u == 0 ? (uint32_t)prev_slot * 1024u + (U - 1) * SOFF : a0 + (u - 1) * SOFF);
    }
    wg_commit();
#pragma unroll
    for (int i = 0; i < NP; i++) {
      const float x = 2 * i < ATT_EARLY ? e[2 * i < ATT_EARLY ? 2 * i : 0] : ex2_approx(S[u & 1][2 * i]);
      const float y = 2 * i + 1 < ATT_EARLY ? e[2 * i + 1 < ATT_EARLY ? 2 * i + 1 : 0] : ex2_approx(S[u & 1][2 * i + 1]);
      P[u & 1][i] = pack_bf16(x, y);
    }
  };
  {
    const KvRing nx = r.next();
    static_for<U>([&](auto uc) {
      constexpr bool first = decltype(uc)::value == 0;
      step(uc, std::true_type{}, std::integral_constant<bool, first>{}, nx);
    });
    prev_slot = r.slot;
    r = nx;
  }
#pragma unroll 1
  for (int st = 1; st < 15; st++) {
    const KvRing nx = r.next();
    static_for<U>([&](auto uc) { step(uc, std::true_type{}, std::false_type{}, nx); });
    prev_slot = r.slot;
    r = nx;
  }
  tail_hook();
  static_for<U>([&](auto uc) {
    constexpr bool more = decltype(uc)::value != U - 1;
    step(uc, std::integral_constant<bool, more>{}, std::false_type{}, r);
  });
  wg_fence();
  pv(P[(U - 1) & 1], (uint32_t)r.slot * 1024u + (U - 1) * SOFF);
  wg_commit();
  wg_wait<0>();
  release(r.slot);
  r.advance();
  fence_regs(o);
}

template <class Release, class Tail>
__device__ __forceinline__ void attn_item_safe(float (&o)[20], const uint32_t (&q)[8], uint32_t sb, KvRing& r, Release&& release, Tail&& tail_hook) {
  float m0 = -INFINITY, m1 = -INFINITY;
#pragma unroll 1
  for (int j = 0; j < 32; j++) {
    if (j == 30) tail_hook();
    if ((j & 1) == 0) mbar_wait(sb + B_KFULL + 8 * r.slot, r.phase);
    const uint32_t cur = sb + S_KV + r.slot * 16384 + (j & 1) * 4096;
    float s[32];
    uint32_t p[16];
    wg_fence();
    wgmma_rs_n64_z<HI_SW64_512>(s, q[0], q[1], q[2], q[3], desc_lo(cur, 16));
    wgmma_rs_n64<HI_SW64_512>(s, q[4], q[5], q[6], q[7], desc_lo(cur, 16) + 2);
    wg_commit();
    wg_wait<0>();
    fence_regs(s);
    float n0r = m0, n1r = m1;
#pragma unroll
    for (int i = 0; i < 8; i++) {
      n0r = fmaxf(n0r, fmaxf(s[4 * i], s[4 * i + 1]));
      n1r = fmaxf(n1r, fmaxf(s[4 * i + 2], s[4 * i + 3]));
    }
    n0r = fmaxf(n0r, __shfl_xor_sync(0xffffffffu, n0r, 1));
    n1r = fmaxf(n1r, __shfl_xor_sync(0xffffffffu, n1r, 1));
    n0r = fmaxf(n0r, __shfl_xor_sync(0xffffffffu, n0r, 2));
    n1r = fmaxf(n1r, __shfl_xor_sync(0xffffffffu, n1r, 2));
    const float c0 = exp2f(m0 - n0r), c1 = exp2f(m1 - n1r);
    m0 = n0r; m1 = n1r;
#pragma unroll
    for (int i = 0; i < 5; i++) { o[4 * i] *= c0; o[4 * i + 1] *= c0; o[4 * i + 2] *= c1; o[4 * i + 3] *= c1; }
#pragma unroll
    for (int i = 0; i < 8; i++) {
      p[2 * i] = pack_bf16(ex2_approx(s[4 * i] - m0), ex2_approx(s[4 * i + 1] - m0));
      p[2 * i + 1] = pack_bf16(ex2_approx(s[4 * i + 2] - m1), ex2_approx(s[4 * i + 3] - m1));
    }
    fence_regs(o);
    wg_fence();
    const uint32_t v = cur + 8192;
    const uint32_t d0 = desc_lo(v, sb + S_ONES - v);
#pragma unroll
    for (int k = 0; k < 4; k++)
      wgmma_rs_n40_tb<HI_SW64_512>(o, p[4 * k], p[4 * k + 1], p[4 * k + 2], p[4 * k + 3], d0 + 64u * k - ((64u * k) << 16));
    wg_commit();
    wg_wait<0>();
    fence_regs(o);
    if (j & 1) { release(r.slot); r.advance(); }
  }
}

struct GPipe {
  int slot; uint32_t mask;
  __device__ __forceinline__ uint32_t parity() const { return (mask >> slot) & 1u; }
  __device__ __forceinline__ void advance(int n) { mask ^= 1u << slot; slot = slot + 1 >= n ? 0 : slot + 1; }
};
__device__ __forceinline__ uint32_t g_slot_off(int slot) {
  return slot < G_STAGES ? (uint32_t)slot * G_STAGE : (slot == G_STAGES ? (uint32_t)S_STG : (uint32_t)S_KV);
}
template <bool AIMG, bool FIRST>
__device__ __forceinline__ void gemm_mma1(float (&a)[64], uint32_t da, uint32_t db) {
  constexpr uint32_t HA = AIMG ? HI_SW64_512 : HI_SW128_1024;
  if constexpr (FIRST) wgmma_ss_n128_tb_z<HA, HI_SW128_1024>(a, da, db); else wgmma_ss_n128_tb<HA, HI_SW128_1024>(a, da, db);
}
template <bool AIMG, int GRP, int WAIT, int NST, int KT0, int KT1>
__device__ __forceinline__ void gemm_stages(float (&a0)[64], float (&a1)[64], uint32_t sb, GPipe& r, int tid, uint32_t rank) {
  constexpr uint32_t MH = AIMG ? 256 : 512;
  const uint32_t da0 = desc_lo(sb, 16), db0 = desc_lo(sb + 16384, 4096);
  int prev = r.slot;
  auto release = [&](int s) { mbar_arrive_pair(sb + B_GEMPTY + 8 * s, tid, rank); };
  auto stage = [&](auto first_c, auto head_c) {
    constexpr bool first = decltype(first_c)::value;
    constexpr bool head = decltype(head_c)::value;
    mbar_wait(sb + B_GFULL + 8 * r.slot, r.parity());
    const uint32_t off = (NST == G_STAGES ? (uint32_t)r.slot * G_STAGE : g_slot_off(r.slot)) >> 4;
    static_for<4>([&](auto kc) {
      constexpr int ks = decltype(kc)::value;
      constexpr uint32_t oa = AIMG ? (ks >> 1) * 512 + (ks & 1) * 2 : ks * 2;
      constexpr uint32_t ob = (ks >> 1) * 512 + (ks & 1) * 128;
      if constexpr (ks % GRP == 0) wg_fence();
      gemm_mma1<AIMG, first && ks == 0>(a0, da0 + off + oa, db0 + off + ob);
      gemm_mma1<AIMG, first && ks == 0>(a1, da0 + off + oa + MH, db0 + off + ob);
      if constexpr (ks % GRP == GRP - 1) {
        wg_commit();
        wg_wait<WAIT>();
        if constexpr (WAIT == 1 && ks == GRP - 1 && !head) release(prev);
      }
    });
    if constexpr (WAIT == 0) release(r.slot);
    prev = r.slot;
    r.advance(NST);
  };
  stage(std::integral_constant<bool, KT0 == 0>{}, std::true_type{});
#pragma unroll 1
  for (int kt = KT0 + 1; kt < KT1; kt++) stage(std::false_type{}, std::false_type{});
  if constexpr (WAIT == 1) { wg_wait<0>(); release(prev); }
}

__device__ __forceinline__ void stage_slot(uint32_t stg, int s, int m, int wq, int lane, const uint32_t (&p)[8]) {
  const int row = m * 64 + wq * 16 + (lane & 7) + ((lane >> 3) & 1) * 8;
  const uint32_t a = stg + s * 8192 + row * 64;
  const int sw = (row >> 1) & 3, ch = lane >> 4;
  stmatrix_x4(a + ((ch ^ sw) << 4), p[0], p[1], p[2], p[3]);
  stmatrix_x4(a + (((ch + 2) ^ sw) << 4), p[4], p[5], p[6], p[7]);
}
__device__ __forceinline__ void stage_slot_box(uint32_t stg, int s, int m, int wq, int lane, const uint32_t (&p)[8]) {
  const int row = m * 64 + wq * 16 + (lane & 7) + ((lane >> 3) & 1) * 8;
  const uint32_t a = stg + (s >> 1) * 16384 + row * 128;
  const int sw = row & 7, ch = (s & 1) * 4 + (lane >> 4);
  stmatrix_x4(a + ((ch ^ sw) << 4), p[0], p[1], p[2], p[3]);
  stmatrix_x4(a + (((ch + 2) ^ sw) << 4), p[4], p[5], p[6], p[7]);
}

#define BQ_BATCH 2
#ifndef M_HOLD
#define M_HOLD 8
#endif
#ifndef M_GRP
#define M_GRP 2
#endif
#ifndef M_WAIT
#define M_WAIT 0
#endif
#ifndef M_GRPB
#define M_GRPB M_GRP
#endif
#ifndef M_WAITB
#define M_WAITB M_WAIT
#endif
#ifndef M_GRPO
#define M_GRPO M_GRP
#endif
#ifndef M_WAITO
#define M_WAITO M_WAIT
#endif
#ifndef M_GRPA
#define M_GRPA 1
#endif
#ifndef M_WAITA
#define M_WAITA 1
#endif
#ifndef M_GRP0
#define M_GRP0 1
#endif
#ifndef M_WAIT0
#define M_WAIT0 1
#endif

__device__ __forceinline__ void tile_n128(const Tile& t, int i, bool last_late, uint32_t sb, uint8_t* smem, GPipe& r, int warp, int lane, uint32_t rank) {
  const int wq = warp & 3, tid = threadIdx.x & 127;
  const int qd = lane & 3, r8 = lane >> 2;
  const uint32_t stg = sb + S_STG;
  float a0[64], a1[64];
  if (i == 0) {
    gemm_stages<false, M_GRP0, M_WAIT0, G_STAGES0, 0, 16>(a0, a1, sb, r, tid, rank);
    r.slot = 0;
    if (tid < 2) mbar_arrive_cluster(sb + B_T0DONE, tid);
  } else if (t.type == T_AOUT) {
    gemm_stages<true, M_GRPO, M_WAITO, G_STAGES, 0, 8>(a0, a1, sb, r, tid, rank);
    if (last_late) gemm_stages<true, M_GRP0, M_WAIT0, G_STAGES0, 8, 16>(a0, a1, sb, r, tid, rank);
    else gemm_stages<true, M_GRPO, M_WAITO, G_STAGES, 8, 16>(a0, a1, sb, r, tid, rank);
  } else if (t.type == T_BOUT) {
    gemm_stages<true, M_GRPO, M_WAITO, G_STAGES, 0, 16>(a0, a1, sb, r, tid, rank);
  } else {
    gemm_stages<false, M_GRP, M_WAIT, G_STAGES, 0, 16>(a0, a1, sb, r, tid, rank);
  }
  fence_regs(a0); fence_regs(a1);
  if (tid == 0) TIMR(0, 3 * i + 1);
  if (i > 0) mbar_wait(sb + B_SFREE, (i - 1) & 1);
  if (t.type <= T_AQ) {
    const float sc = t.type == T_AQ ? QSCALE : 1.f;
    float* stat = reinterpret_cast<float*>(smem + S_STAT);
    static_for<4>([&](auto sc_) {
      constexpr int s = decltype(sc_)::value;
      static_for<2>([&](auto mc) {
        constexpr int m = decltype(mc)::value;
        float (&a)[64] = m == 0 ? a0 : a1;
        float s0 = 0.f, s1 = 0.f;
        uint32_t p[8];
#pragma unroll
        for (int j = 0; j < 4; j++) {
          const int b = (s * 4 + j) * 4;
          const float x0 = a[b] * sc, x1 = a[b + 1] * sc, x2 = a[b + 2] * sc, x3 = a[b + 3] * sc;
          s0 = fmaf(x0, x0, s0); s0 = fmaf(x1, x1, s0);
          s1 = fmaf(x2, x2, s1); s1 = fmaf(x3, x3, s1);
          p[2 * j] = pack_bf16(x0, x1);
          p[2 * j + 1] = pack_bf16(x2, x3);
        }
        stage_slot(stg, s, m, wq, lane, p);
        s0 += __shfl_xor_sync(0xffffffffu, s0, 1);
        s1 += __shfl_xor_sync(0xffffffffu, s1, 1);
        s0 += __shfl_xor_sync(0xffffffffu, s0, 2);
        s1 += __shfl_xor_sync(0xffffffffu, s1, 2);
        const uint32_t mx = __reduce_max_sync(0xffffffffu, max(__float_as_uint(s0), __float_as_uint(s1)));
        if (lane == 0) stat[s * 8 + m * 4 + wq] = __uint_as_float(mx);
      });
    });
  } else
  if (t.type == T_BKV) {
    static_for<4>([&](auto sc_) {
      constexpr int s = decltype(sc_)::value;
      static_for<2>([&](auto mc) {
        constexpr int m = decltype(mc)::value;
        float (&a)[64] = m == 0 ? a0 : a1;
        uint32_t p[8];
#pragma unroll
        for (int j = 0; j < 4; j++) {
          const int b = (s * 4 + j) * 4;
          float x0 = a[b], x1 = a[b + 1], x2 = a[b + 2], x3 = a[b + 3];
          if constexpr (s < 2) { x0 = phi_fn(x0); x1 = phi_fn(x1); x2 = phi_fn(x2); x3 = phi_fn(x3); }
          p[2 * j] = pack_bf16(x0, x1);
          p[2 * j + 1] = pack_bf16(x2, x3);
        }
        stage_slot(stg, s, m, wq, lane, p);
      });
    });
    fence_proxy_async_smem();
    named_bar_sync(1, 128);
    float d[2][20];
    wg_fence();
    static_for<2>([&](auto hc) {
      constexpr int hh = decltype(hc)::value;
      const uint32_t tb = stg + (2 + hh) * 8192;
      const uint32_t la = desc_lo(stg, 8192), lb = desc_lo(tb, sb + S_ONES - tb);
      wgmma_ss_n40_tb_ta_z<HI_SW64_512, HI_SW64_512>(d[hh], la, lb);
#pragma unroll
      for (int k = 1; k < 8; k++)
        wgmma_ss_n40_tb_ta<HI_SW64_512, HI_SW64_512>(d[hh], la + 64u * k, lb + 64u * k - ((64u * k) << 16));
    });
    wg_commit();
    wg_wait<0>();
    named_bar_sync(1, 128);
    fence_regs(d[0]); fence_regs(d[1]);
    {
      const int hh = wq >> 1;
      float* dst = reinterpret_cast<float*>(smem + S_STG + hh * 8192) + ((wq & 1) * 16 + r8) * 40 + 2 * qd;
#pragma unroll
      for (int j = 0; j < 5; j++) {
        *reinterpret_cast<float2*>(dst + 8 * j) = hh ? make_float2(d[1][4 * j], d[1][4 * j + 1]) : make_float2(d[0][4 * j], d[0][4 * j + 1]);
        *reinterpret_cast<float2*>(dst + 8 * 40 + 8 * j) = hh ? make_float2(d[1][4 * j + 2], d[1][4 * j + 3]) : make_float2(d[0][4 * j + 2], d[0][4 * j + 3]);
      }
    }
  } else if (t.type == T_BQ) {
    uint32_t pq[2][4][8];
    static_for<4>([&](auto sc_) {
      constexpr int s = decltype(sc_)::value;
      static_for<2>([&](auto mc) {
        constexpr int m = decltype(mc)::value;
        float (&a)[64] = m == 0 ? a0 : a1;
#pragma unroll
        for (int j = 0; j < 4; j++) {
          const int b = (s * 4 + j) * 4;
          pq[m][s][2 * j] = pack_bf16(phi_fn(a[b]), phi_fn(a[b + 1]));
          pq[m][s][2 * j + 1] = pack_bf16(phi_fn(a[b + 2]), phi_fn(a[b + 3]));
        }
      });
    });
    mbar_wait(sb + B_GFULL + 8 * r.slot, r.parity());
    const uint32_t kvd = desc_lo(sb + r.slot * G_STAGE, 640);
    static_for<4 / BQ_BATCH>([&](auto pc) {
      constexpr int sp = decltype(pc)::value;
      float d[BQ_BATCH][2][20];
      wg_fence();
      static_for<BQ_BATCH>([&](auto sc_) {
        constexpr int ss = decltype(sc_)::value, s = BQ_BATCH * sp + ss;
        static_for<2>([&](auto mc) {
          constexpr int m = decltype(mc)::value;
          wgmma_rs_n40_tb_z<HI_NOSW_128>(d[ss][m], pq[m][s][0], pq[m][s][1], pq[m][s][2], pq[m][s][3], kvd + s * 160);
          wgmma_rs_n40_tb<HI_NOSW_128>(d[ss][m], pq[m][s][4], pq[m][s][5], pq[m][s][6], pq[m][s][7], kvd + s * 160 + 80);
        });
      });
      wg_commit();
      wg_wait<0>();
      static_for<BQ_BATCH>([&](auto sc_) {
        constexpr int ss = decltype(sc_)::value, s = BQ_BATCH * sp + ss;
        static_for<2>([&](auto mc) {
          constexpr int m = decltype(mc)::value;
          fence_regs(d[ss][m]);
          const float i0 = rcp_approx(d[ss][m][16] + 1e-6f), i1 = rcp_approx(d[ss][m][18] + 1e-6f);
          uint32_t p[8];
#pragma unroll
          for (int j = 0; j < 4; j++) {
            p[2 * j] = pack_bf16(d[ss][m][4 * j] * i0, d[ss][m][4 * j + 1] * i0);
            p[2 * j + 1] = pack_bf16(d[ss][m][4 * j + 2] * i1, d[ss][m][4 * j + 3] * i1);
          }
          stage_slot(stg, s, m, wq, lane, p);
        });
      });
    });
    if (tid < 2) mbar_arrive_cluster(sb + B_GEMPTY + 8 * r.slot, tid);
    r.advance(G_STAGES);
  } else {
    static_for<4>([&](auto sc_) {
      constexpr int s = decltype(sc_)::value;
      static_for<2>([&](auto mc) {
        constexpr int m = decltype(mc)::value;
        float (&a)[64] = m == 0 ? a0 : a1;
        uint32_t p[8];
#pragma unroll
        for (int j = 0; j < 4; j++) {
          const int b = (s * 4 + j) * 4;
          p[2 * j] = pack_bf16(a[b], a[b + 1]);
          p[2 * j + 1] = pack_bf16(a[b + 2], a[b + 3]);
        }
        stage_slot_box(stg, s, m, wq, lane, p);
      });
    });
  }
}

#define HWAIT mbar_wait_long
__global__ void __cluster_dims__(2, 1, 1) __launch_bounds__(512, 1) mega_kernel(const __grid_constant__ MegaParams prm) {
  extern __shared__ uint8_t smem_raw[];
  const uint32_t sb = (smem_u32(smem_raw) + 1023) & ~1023u;
  uint8_t* smem = smem_raw + (sb - smem_u32(smem_raw));
  const int warp = uniform_warp_id(), lane = threadIdx.x & 31;
  const uint32_t rank = cluster_rank();
  const int pair = blockIdx.x >> 1;

  if (threadIdx.x == 0) {
    for (int s = 0; s < G_STAGES0; s++) { mbar_init(sb + B_GFULL + 8 * s, 1); mbar_init(sb + B_GEMPTY + 8 * s, 2); }
    mbar_init(sb + B_T0DONE, 2); mbar_init(sb + B_LFREE, 2); mbar_init(sb + B_ADONE, 4);
    for (int s = 0; s < KV_STAGES; s++) { mbar_init(sb + B_KFULL + 8 * s, 1); mbar_init(sb + B_KEMPTY + 8 * s, KV_MC ? 4 : 2); }
    mbar_init(sb + B_SFULL, 128); mbar_init(sb + B_SFREE, 1);
    for (int w = 0; w < 2; w++) { mbar_init(sb + B_OFULL + 8 * w, 128); mbar_init(sb + B_OFREE + 8 * w, 1); }
    mbar_init(sb + B_RDY, 1); mbar_init(sb + B_VERD, 1);
    fence_mbar_init();
  }
  if (threadIdx.x < 256) reinterpret_cast<uint32_t*>(smem + S_ONES)[threadIdx.x] = 0x3F803F80u;
  fence_proxy_async_smem();
  __syncthreads();
  cluster_sync();

  if (warp < 4) {
    reg_dealloc<M_PREGS>();
    const uint32_t epoch = *reinterpret_cast<volatile uint32_t*>(&g_epoch);
    if (warp == 0) {
      if (lane == 0) {
        GPipe r{0, 0xffffffffu};
        for (int i = 0; i < MAXT; i++) {
          const Tile t = decode_tile(prm.gt[pair][i]);
          if (t.type == T_NONE) break;
          const int rb = t.mp * 2 + (int)rank;
          const CUtensorMap* mw; int c0, c2;
          if (t.type == T_AKV || t.type == T_BKV) { mw = &prm.wkv[t.type == T_BKV]; c0 = 64 * t.idx; c2 = 1; }
          else { mw = &prm.wblk[t.type == T_AQ ? 0 : t.type == T_BQ ? 1 : t.type - 2]; c0 = 0; c2 = 2 * t.idx; }
          const bool isout = t.type >= T_BOUT;
          const CUtensorMap* ma = &prm.x[t.type <= T_AQ ? 0 : 1];
          const uint8_t* img = g_o + (size_t)((t.type == T_BOUT ? 16 : 0) + rb) * NH * 8192;
          const bool last_late = t.type == T_AOUT && t.mp >= 4;
          if (t.type == T_BOUT) cnt_wait(C_BQ + t.mp, epoch, 16);
          for (int kt = 0; kt < 16; kt++) {
            if (t.type == T_AOUT && (kt & 7) == 0) cnt_wait(C_ATT + t.mp * 2 + (kt >> 3), epoch, 64);
            const bool wide = i == 0 || (last_late && kt >= 8);
            if (last_late && kt == 8) {
              HWAIT(sb + B_ADONE, 0);
              HWAIT(sb + B_LFREE, 0);
            }
#if M_HOLD >= 0
            if (i == 1 && kt == M_HOLD && prm.na[pair] > 0) HWAIT(sb + B_VERD, 0);
#endif
            mbar_wait(sb + B_GEMPTY + 8 * r.slot, r.parity());
            const uint32_t full = sb + B_GFULL + 8 * r.slot, sa = sb + g_slot_off(r.slot);
            mbar_expect_tx(full, 32768);
            tma_load_3d_mc(sa + 16384 + rank * 8192, mw, full, c0, kt * 64 + (int)rank * 32, c2, (uint16_t)3);
            if (isout) bulk_load_1d(sa, img + kt * 16384, 16384, full);
            else tma_load_2d(sa, ma, full, kt * 64, rb * 128);
            r.advance(wide ? G_STAGES0 : G_STAGES);
          }
          if (i == 0) r.slot = 0;
          if (t.type == T_BQ) {
            cnt_wait2(C_KVB + 2 * t.idx, 1, C_KVB + 2 * t.idx + 1, 1, epoch);
            HWAIT(sb + B_GEMPTY + 8 * r.slot, r.parity());
            const uint32_t full = sb + B_GFULL + 8 * r.slot;
            mbar_expect_tx(full, 4 * 2560);
            bulk_load_1d(sb + r.slot * G_STAGE, g_kvb + t.idx * 4 * 640, 4 * 2560, full);
            r.advance(G_STAGES);
          }
        }
      }
    } else if (warp == 1) {
      const int na = prm.na[pair];
      KvRing r{0, 1};
      if (lane == 0 && na > 0) HWAIT(sb + B_T0DONE, 0);
      for (int it = 0; it < na; it++) {
        const int h = prm.at[pair][it] & 31, mp = prm.at[pair][it] >> 5;
        const uint8_t* src = g_qkv + (size_t)((1 + rank) * NH + h) * SEQ * 64;
        auto load_stage = [&](int j) {
          HWAIT(sb + B_KEMPTY + 8 * r.slot, r.phase);
          const uint32_t full = sb + B_KFULL + 8 * r.slot;
          mbar_expect_tx(full, 16384);
          if (KV_MC) {
            bulk_load_1d_mc(sb + S_KV + r.slot * 16384 + rank * 8192, src + j * 8192, 8192, full, (uint16_t)3);
          } else {
            const uint8_t* ks = g_qkv + (size_t)(NH + h) * SEQ * 64 + j * 8192;
            bulk_load_1d(sb + S_KV + r.slot * 16384, ks, 8192, full);
            bulk_load_1d(sb + S_KV + r.slot * 16384 + 8192, ks + (size_t)NH * SEQ * 64, 8192, full);
          }
          r.advance();
        };
        if (lane == 0) {
          cnt_wait2(C_AKV + (h >> 1), 16, C_AQ + (h >> 2) * 8 + mp, 2, epoch);
          TIMR(3, 4 * it);
          mbar_arrive(sb + B_RDY);
          load_stage(0);
          TIMR(3, 4 * it + 1);
        }
        __syncwarp();
        {
          const uint4 kq = __ldcg(reinterpret_cast<const uint4*>(g_stats + (NH + h) * 128) + lane);
          const uint4 vq = __ldcg(reinterpret_cast<const uint4*>(g_stats + (2 * NH + h) * 128) + lane);
          const uint4 qq = __ldcg(reinterpret_cast<const uint4*>(g_stats + h * 128 + mp * 16 + rank * 8) + (lane & 1));
          const float km = __uint_as_float(__reduce_max_sync(0xffffffffu, max(max(kq.x, kq.y), max(kq.z, kq.w))));
          const float vm = __uint_as_float(__reduce_max_sync(0xffffffffu, max(max(vq.x, vq.y), max(vq.z, vq.w))));
          const float qm = __uint_as_float(max(max(qq.x, qq.y), max(qq.z, qq.w)));
          const bool ok = (qm * km <= 4000.f) && (vm <= 1.0e21f) && (vm >= 3.0e-17f);
          if (lane < 2) reinterpret_cast<volatile uint32_t*>(smem + S_FAST)[it * 2 + lane] = ok ? 1u : 0u;
          __syncwarp();
          if (lane == 0) { mbar_arrive(sb + B_VERD); TIMR(3, 4 * it + 2); }
        }
        if (lane == 0) { for (int j = 1; j < 16; j++) load_stage(j); }
        __syncwarp();
      }
    } else if (warp == 2) {
      const uint32_t stg = sb + S_STG;
      for (int i = 0; i < MAXT; i++) {
        const Tile t = decode_tile(prm.gt[pair][i]);
        if (t.type == T_NONE) break;
        const int rb = t.mp * 2 + (int)rank;
        uint32_t last = 0;
        if (lane == 0) {
          HWAIT(sb + B_SFULL, i & 1);
          TIMR(2, 4 * i);
          if (t.type <= T_AQ) {
            for (int s = 0; s < 4; s++) {
              const int ph = t.type == T_AQ ? 4 * t.idx + s : (1 + (s >> 1)) * NH + 2 * t.idx + (s & 1);
              bulk_store_1d(g_qkv + ((size_t)ph * SEQ + rb * 128) * 64, stg + s * 8192, 8192);
              bulk_store_1d(g_stats + ph * 128 + rb * 8, sb + S_STAT + s * 32, 32);
            }
          } else if (t.type == T_BKV) {
            for (int s = 0; s < 2; s++) bulk_reduce_add_f32(g_kv + (2 * t.idx + s) * 1280, stg + s * 8192, 5120);
          } else if (t.type == T_BQ) {
            bulk_store_1d(g_o + (size_t)((16 + rb) * NH + 4 * t.idx) * 8192, stg, 4 * 8192);
          } else {
            for (int s = 0; s < 2; s++) tma_store_2d(&prm.out, stg + s * 16384, (t.type == T_BOUT ? DM : 0) + t.idx * 128 + s * 64, rb * 128);
          }
          bulk_commit();
          bulk_wait_read<0>();
          TIMR(2, 4 * i + 1);
          mbar_arrive(sb + B_SFREE);
          if (i == MAXT - 2) { mbar_arrive_cluster(sb + B_LFREE, 0); mbar_arrive_cluster(sb + B_LFREE, 1); }
          if (t.type < T_BOUT) {
            bulk_wait<0>();
            TIMR(2, 4 * i + 2);
            const int c = t.type == T_AKV ? C_AKV + t.idx : t.type == T_AQ ? C_AQ + t.idx * 8 + t.mp : t.type == T_BKV ? C_BKV + t.idx : C_BQ + t.mp;
            if (t.type == T_BKV) last = cnt_add(c) + 1 == epoch * 16 + 16 ? 1u : 0u;
            else cnt_red(c, 1);
            TIMR(2, 4 * i + 3);
          }
        }
        last = __shfl_sync(0xffffffffu, last, 0);
        if (last) {
          asm volatile("fence.acq_rel.gpu;" ::: "memory");
          fence_proxy_async_all();
#pragma unroll 2
          for (int c = lane; c < 320; c += 32) {
            const int hh = c / 160, rr = c % 160, d = rr / 5, g = rr % 5;
            float4* src = reinterpret_cast<float4*>(g_kv + (2 * t.idx + hh) * 1280 + d * 40 + g * 8);
            const float4 a = __ldcg(src), b = __ldcg(src + 1);
            uint4 v;
            v.x = pack_bf16(a.x, a.y); v.y = pack_bf16(a.z, a.w); v.z = pack_bf16(b.x, b.y); v.w = pack_bf16(b.z, b.w);
            *reinterpret_cast<uint4*>(g_kvb + (2 * t.idx + hh) * 640 + (d >> 3) * 160 + g * 32 + (d & 7) * 4) = v;
            __stcg(src, make_float4(0.f, 0.f, 0.f, 0.f)); __stcg(src + 1, make_float4(0.f, 0.f, 0.f, 0.f));
          }
          __threadfence();
          fence_proxy_async_all();
          __syncwarp();
          if (lane == 0) cnt_red(C_KVB + t.idx, 1);
        }
        __syncwarp();
      }
      if (lane == 0) bulk_wait<0>();
    } else {
      if (lane == 0) {
        const int na = prm.na[pair];
        for (int it = 0; it < na; it++) {
          const int h = prm.at[pair][it] & 31, mp = prm.at[pair][it] >> 5;
          uint8_t* dst = g_o + (size_t)((mp * 2 + rank) * NH + h) * 8192;
          for (int w = 0; w < 2; w++) {
            HWAIT(sb + B_OFULL + 8 * w, it & 1);
            bulk_store_1d(dst + w * 4096, sb + S_OST + w * 4096, 4096);
            bulk_commit();
          }
          bulk_wait_read<0>();
          mbar_arrive(sb + B_OFREE); mbar_arrive(sb + B_OFREE + 8);
          bulk_wait<0>();
          cnt_red(C_ATT + mp * 2 + (h >> 4), 2);
        }
      }
    }
    __syncwarp();
    cluster_sync();
    if (threadIdx.x == 0) {
      if (atomicAdd(&g_exit, 1u) == gridDim.x - 1) { g_exit = 0; __threadfence(); atomicAdd(&g_epoch, 1u); }
    }
  } else if (warp < 12) {
    if constexpr (M_AREGS > 128) reg_alloc<M_AREGS>(); else reg_dealloc<M_AREGS>();
    const int wg = (warp >> 2) - 1, wq = warp & 3, tid = threadIdx.x & 127;
    const int qd = lane & 3, r8 = lane >> 2;
    const int na = prm.na[pair];
    auto release = [&](int slot) {
      if (KV_MC) mbar_arrive_pair(sb + B_KEMPTY + 8 * slot, tid, rank);
      else if (tid == 0) mbar_arrive(sb + B_KEMPTY + 8 * slot);
    };
    auto load_q = [&](uint32_t (&q)[8], int it) {
      const int h = prm.at[pair][it] & 31, mp = prm.at[pair][it] >> 5;
      const int row = mp * 256 + (int)rank * 128 + wg * 64 + wq * 16 + r8;
      const uint8_t* qp = g_qkv + ((size_t)h * SEQ + row) * 64 + qd * 4;
      const int sw = (row >> 1) & 3;
#pragma unroll
      for (int ks = 0; ks < 2; ks++) {
        q[4 * ks + 0] = __ldcg(reinterpret_cast<const uint32_t*>(qp + (((2 * ks) ^ sw) << 4)));
        q[4 * ks + 1] = __ldcg(reinterpret_cast<const uint32_t*>(qp + (((2 * ks) ^ sw) << 4) + 512));
        q[4 * ks + 2] = __ldcg(reinterpret_cast<const uint32_t*>(qp + (((2 * ks + 1) ^ sw) << 4)));
        q[4 * ks + 3] = __ldcg(reinterpret_cast<const uint32_t*>(qp + (((2 * ks + 1) ^ sw) << 4) + 512));
      }
    };
    uint32_t q[8], qn[8];
    KvRing r{0, 0};
    if (na > 0) {
      mbar_wait(sb + B_RDY, 0);
      load_q(q, 0);
    }
    for (int it = 0; it < na; it++) {
      if (tid == 0 && wg == 0) TIMR(1, 2 * it);
      mbar_wait(sb + B_VERD, it & 1);
      mbar_wait(sb + B_KFULL + 8 * r.slot, r.phase);
      const bool fast = __all_sync(0xffffffffu, reinterpret_cast<volatile uint32_t*>(smem + S_FAST)[it * 2 + wg] != 0);
      float o[20];
#pragma unroll
      for (int i = 0; i < 20; i++) o[i] = 0.f;
      fence_regs(o);
      auto tail_hook = [&]() {
        if (it + 1 < na) {
          mbar_wait(sb + B_RDY, (it + 1) & 1);
          load_q(qn, it + 1);
        }
      };
      if (fast) attn_item_fast(o, q, sb, r, release, tail_hook);
      else attn_item_safe(o, q, sb, r, release, tail_hook);
      const float i0 = rcp_approx(o[16]), i1 = rcp_approx(o[18]);
      uint32_t p[8];
#pragma unroll
      for (int j = 0; j < 4; j++) {
        p[2 * j] = pack_bf16(o[4 * j] * i0, o[4 * j + 1] * i0);
        p[2 * j + 1] = pack_bf16(o[4 * j + 2] * i1, o[4 * j + 3] * i1);
      }
      if (it > 0) mbar_wait(sb + B_OFREE + 8 * wg, (it - 1) & 1);
      stage_slot(sb + S_OST + wg * 4096, 0, 0, wq, lane, p);
      fence_proxy_async_smem();
      mbar_arrive(sb + B_OFULL + 8 * wg);
#pragma unroll
      for (int i = 0; i < 8; i++) q[i] = qn[i];
      if (tid == 0 && wg == 0) TIMR(1, 2 * it + 1);
    }
    if (tid < 2) mbar_arrive_cluster(sb + B_ADONE, tid);
    __syncwarp();
    cluster_sync();
  } else {
    reg_alloc<M_GREGS>();
    GPipe r{0, 0u};
    for (int i = 0; i < MAXT; i++) {
      const Tile t = decode_tile(prm.gt[pair][i]);
      if (t.type == T_NONE) break;
      if ((threadIdx.x & 127) == 0) TIMR(0, 3 * i);
      tile_n128(t, i, t.type == T_AOUT && t.mp >= 4, sb, smem, r, warp, lane, rank);
      fence_proxy_async_smem();
      mbar_arrive(sb + B_SFULL);
      if ((threadIdx.x & 127) == 0) TIMR(0, 3 * i + 2);
    }
    __syncwarp();
    cluster_sync();
  }
}
#include <string.h>

typedef CUresult (*PFN_encodeTiled)(CUtensorMap*, CUtensorMapDataType, cuuint32_t, void*, const cuuint64_t*, const cuuint64_t*,
                                    const cuuint32_t*, const cuuint32_t*, CUtensorMapInterleave, CUtensorMapSwizzle,
                                    CUtensorMapL2promotion, CUtensorMapFloatOOBfill);

static PFN_encodeTiled get_encode() {
  static PFN_encodeTiled fn = nullptr;
  if (!fn) {
    void* p = nullptr;
    cudaDriverEntryPointQueryResult q;
    cudaGetDriverEntryPoint("cuTensorMapEncodeTiled", &p, cudaEnableDefault, &q);
    fn = (PFN_encodeTiled)p;
  }
  return fn;
}
static void make_map(CUtensorMap* m, const void* base, int rank, const cuuint64_t* dims, const cuuint64_t* strides, const cuuint32_t* box) {
  cuuint32_t es[3] = {1, 1, 1};
  get_encode()(m, CU_TENSOR_MAP_DATA_TYPE_BFLOAT16, rank, const_cast<void*>(base), dims, strides, box, es, CU_TENSOR_MAP_INTERLEAVE_NONE,
               CU_TENSOR_MAP_SWIZZLE_128B, CU_TENSOR_MAP_L2_PROMOTION_L2_256B, CU_TENSOR_MAP_FLOAT_OOB_FILL_NONE);
}
static void map_2d(CUtensorMap* m, const void* base, int rows, int cols) {
  cuuint64_t dims[2] = {(cuuint64_t)cols, (cuuint64_t)rows};
  cuuint64_t strides[1] = {(cuuint64_t)cols * 2};
  cuuint32_t box[2] = {64, 128};
  make_map(m, base, 2, dims, strides, box);
}
static void map_parts(CUtensorMap* m, const void* base, int np) {
  cuuint64_t dims[3] = {1024, 1024, 3};
  cuuint64_t strides[2] = {3072 * 2, 1024 * 2};
  cuuint32_t box[3] = {64, 32, (cuuint32_t)np};
  make_map(m, base, 3, dims, strides, box);
}
static void map_blk(CUtensorMap* m, const void* base, int N) {
  cuuint64_t dims[3] = {64, 1024, (cuuint64_t)(N / 64)};
  cuuint64_t strides[2] = {(cuuint64_t)N * 2, 128};
  cuuint32_t box[3] = {64, 32, 2};
  make_map(m, base, 3, dims, strides, box);
}

#define SCHED_T3 100000.0
#define SCHED_T4 125000.0
#define SCHED_SLOW 1.8
static void build_schedule(MegaParams& P) {
  auto enc = [](int type, int idx, int mp) { return (uint16_t)(type | (idx << 3) | (mp << 7)); };
  for (int p = 0; p < NPAIR; p++) {
    for (int i = 0; i < MAXT; i++) P.gt[p][i] = T_NONE;
    P.na[p] = 0;
    if (p >= 64) continue;
    const int hi = p >> 3, lo = p & 7;
    int n = 0;
    P.gt[p][n++] = hi < 4 ? enc(T_AKV, hi, lo) : hi < 6 ? enc(T_AQ, hi - 4, lo) : enc(T_AKV, hi - 2, lo);
    P.gt[p][n++] = hi < 2 ? enc(T_AKV, 6 + hi, lo) : hi < 4 ? enc(T_AQ, hi, lo) : enc(T_AKV, 4 + hi, lo);
    P.gt[p][n++] = hi < 4 ? enc(T_AKV, 12 + hi, lo) : enc(T_AQ, hi, lo);
    P.gt[p][n++] = enc(T_BKV, hi, lo);
    P.gt[p][n++] = enc(T_BKV, 8 + hi, lo);
    P.gt[p][n++] = enc(T_BQ, hi, lo);
    if (p < 32) {
      P.gt[p][n++] = enc(T_AOUT, lo, hi);
      P.gt[p][n++] = enc(T_BOUT, lo, 4 + hi);
    } else {
      P.gt[p][n++] = enc(T_BOUT, lo, hi - 4);
      P.gt[p][n++] = enc(T_AOUT, lo, hi);
    }
    for (int r = 0; r < 4; r++) {
      int h, mp;
      if (r < 2) { h = r * 8 + hi; mp = lo; }
      else { h = 16 + (p & 15); mp = (r - 2) * 4 + (p >> 4); }
      P.at[p][P.na[p]++] = (uint8_t)(h | (mp << 5));
    }
  }
}

static void build_params(MegaParams& P, void* const* d_in, void* d_out) {
  map_2d(&P.x[0], d_in[0], SEQ, DM);
  map_2d(&P.x[1], d_in[3], SEQ, DM);
  map_parts(&P.wkv[0], d_in[1], 2);
  map_parts(&P.wkv[1], d_in[4], 2);
  map_blk(&P.wblk[0], d_in[1], 3 * DM);
  map_blk(&P.wblk[1], d_in[4], 3 * DM);
  map_blk(&P.wblk[2], d_in[5], DM);
  map_blk(&P.wblk[3], d_in[2], DM);
  map_2d(&P.out, d_out, SEQ, 2 * DM);
  P.xa = (const uint8_t*)d_in[0]; P.wa = (const uint8_t*)d_in[1];
  build_schedule(P);
}

extern "C" void kernel_launch(void* const* d_in, const int* in_sizes, int n_in, void* d_out, int out_size) {
  static bool attr_done = false;
  if (!attr_done) {
    attr_done = true;
    cudaFuncSetAttribute(mega_kernel, cudaFuncAttributeMaxDynamicSharedMemorySize, MEGA_SMEM);
  }
  MegaParams P;
  memset(&P, 0, sizeof(P));
  build_params(P, d_in, d_out);
  mega_kernel<<<2 * NPAIR, 512, MEGA_SMEM, cudaStreamPerThread>>>(P);
}
```

```cpp
template <uint32_t HA, uint32_t HB>
__device__ __forceinline__ void wgmma_ss_n192_tb(float (&d)[96], uint32_t la, uint32_t lb) {
  asm volatile("{\n.reg .pred p;\n.reg .b64 da, db;\n"
    "mov.b64 da, {%96, %98};\nmov.b64 db, {%97, %99};\n"
    "setp.ne.b32 p, 1, 0;\n"
    "wgmma.mma_async.sync.aligned.m64n192k16.f32.bf16.bf16 "
    "{%0, %1, %2, %3, %4, %5, %6, %7, %8, %9, %10, %11, %12, %13, %14, %15, "
    "%16, %17, %18, %19, %20, %21, %22, %23, %24, %25, %26, %27, %28, %29, %30, %31, "
    "%32, %33, %34, %35, %36, %37, %38, %39, %40, %41, %42, %43, %44, %45, %46, %47, "
    "%48, %49, %50, %51, %52, %53, %54, %55, %56, %57, %58, %59, %60, %61, %62, %63, "
    "%64, %65, %66, %67, %68, %69, %70, %71, %72, %73, %74, %75, %76, %77, %78, %79, "
    "%80, %81, %82, %83, %84, %85, %86, %87, %88, %89, %90, %91, %92, %93, %94, %95}, "
    "da, db, p, 1, 1, 0, 1;\n}\n"
    : "+f"(d[0]), "+f"(d[1]), "+f"(d[2]), "+f"(d[3]), "+f"(d[4]), "+f"(d[5]), "+f"(d[6]), "+f"(d[7]),
      "+f"(d[8]), "+f"(d[9]), "+f"(d[10]), "+f"(d[11]), "+f"(d[12]), "+f"(d[13]), "+f"(d[14]), "+f"(d[15]),
      "+f"(d[16]), "+f"(d[17]), "+f"(d[18]), "+f"(d[19]), "+f"(d[20]), "+f"(d[21]), "+f"(d[22]), "+f"(d[23]),
      "+f"(d[24]), "+f"(d[25]), "+f"(d[26]), "+f"(d[27]), "+f"(d[28]), "+f"(d[29]), "+f"(d[30]), "+f"(d[31]),
      "+f"(d[32]), "+f"(d[33]), "+f"(d[34]), "+f"(d[35]), "+f"(d[36]), "+f"(d[37]), "+f"(d[38]), "+f"(d[39]),
      "+f"(d[40]), "+f"(d[41]), "+f"(d[42]), "+f"(d[43]), "+f"(d[44]), "+f"(d[45]), "+f"(d[46]), "+f"(d[47]),
      "+f"(d[48]), "+f"(d[49]), "+f"(d[50]), "+f"(d[51]), "+f"(d[52]), "+f"(d[53]), "+f"(d[54]), "+f"(d[55]),
      "+f"(d[56]), "+f"(d[57]), "+f"(d[58]), "+f"(d[59]), "+f"(d[60]), "+f"(d[61]), "+f"(d[62]), "+f"(d[63]),
      "+f"(d[64]), "+f"(d[65]), "+f"(d[66]), "+f"(d[67]), "+f"(d[68]), "+f"(d[69]), "+f"(d[70]), "+f"(d[71]),
      "+f"(d[72]), "+f"(d[73]), "+f"(d[74]), "+f"(d[75]), "+f"(d[76]), "+f"(d[77]), "+f"(d[78]), "+f"(d[79]),
      "+f"(d[80]), "+f"(d[81]), "+f"(d[82]), "+f"(d[83]), "+f"(d[84]), "+f"(d[85]), "+f"(d[86]), "+f"(d[87]),
      "+f"(d[88]), "+f"(d[89]), "+f"(d[90]), "+f"(d[91]), "+f"(d[92]), "+f"(d[93]), "+f"(d[94]), "+f"(d[95])
    : "r"(la), "r"(lb), "n"(HA), "n"(HB));
}
template <uint32_t HA, uint32_t HB>
__device__ __forceinline__ void wgmma_ss_n192_tb_z(float (&d)[96], uint32_t la, uint32_t lb) {
  asm volatile("{\n.reg .pred p;\n.reg .b64 da, db;\n"
    "mov.b64 da, {%96, %98};\nmov.b64 db, {%97, %99};\n"
    "setp.ne.b32 p, 0, 0;\n"
    "wgmma.mma_async.sync.aligned.m64n192k16.f32.bf16.bf16 "
    "{%0, %1, %2, %3, %4, %5, %6, %7, %8, %9, %10, %11, %12, %13, %14, %15, "
    "%16, %17, %18, %19, %20, %21, %22, %23, %24, %25, %26, %27, %28, %29, %30, %31, "
    "%32, %33, %34, %35, %36, %37, %38, %39, %40, %41, %42, %43, %44, %45, %46, %47, "
    "%48, %49, %50, %51, %52, %53, %54, %55, %56, %57, %58, %59, %60, %61, %62, %63, "
    "%64, %65, %66, %67, %68, %69, %70, %71, %72, %73, %74, %75, %76, %77, %78, %79, "
    "%80, %81, %82, %83, %84, %85, %86, %87, %88, %89, %90, %91, %92, %93, %94, %95}, "
    "da, db, p, 1, 1, 0, 1;\n}\n"
    : "=f"(d[0]), "=f"(d[1]), "=f"(d[2]), "=f"(d[3]), "=f"(d[4]), "=f"(d[5]), "=f"(d[6]), "=f"(d[7]),
      "=f"(d[8]), "=f"(d[9]), "=f"(d[10]), "=f"(d[11]), "=f"(d[12]), "=f"(d[13]), "=f"(d[14]), "=f"(d[15]),
      "=f"(d[16]), "=f"(d[17]), "=f"(d[18]), "=f"(d[19]), "=f"(d[20]), "=f"(d[21]), "=f"(d[22]), "=f"(d[23]),
      "=f"(d[24]), "=f"(d[25]), "=f"(d[26]), "=f"(d[27]), "=f"(d[28]), "=f"(d[29]), "=f"(d[30]), "=f"(d[31]),
      "=f"(d[32]), "=f"(d[33]), "=f"(d[34]), "=f"(d[35]), "=f"(d[36]), "=f"(d[37]), "=f"(d[38]), "=f"(d[39]),
      "=f"(d[40]), "=f"(d[41]), "=f"(d[42]), "=f"(d[43]), "=f"(d[44]), "=f"(d[45]), "=f"(d[46]), "=f"(d[47]),
      "=f"(d[48]), "=f"(d[49]), "=f"(d[50]), "=f"(d[51]), "=f"(d[52]), "=f"(d[53]), "=f"(d[54]), "=f"(d[55]),
      "=f"(d[56]), "=f"(d[57]), "=f"(d[58]), "=f"(d[59]), "=f"(d[60]), "=f"(d[61]), "=f"(d[62]), "=f"(d[63]),
      "=f"(d[64]), "=f"(d[65]), "=f"(d[66]), "=f"(d[67]), "=f"(d[68]), "=f"(d[69]), "=f"(d[70]), "=f"(d[71]),
      "=f"(d[72]), "=f"(d[73]), "=f"(d[74]), "=f"(d[75]), "=f"(d[76]), "=f"(d[77]), "=f"(d[78]), "=f"(d[79]),
      "=f"(d[80]), "=f"(d[81]), "=f"(d[82]), "=f"(d[83]), "=f"(d[84]), "=f"(d[85]), "=f"(d[86]), "=f"(d[87]),
      "=f"(d[88]), "=f"(d[89]), "=f"(d[90]), "=f"(d[91]), "=f"(d[92]), "=f"(d[93]), "=f"(d[94]), "=f"(d[95])
    : "r"(la), "r"(lb), "n"(HA), "n"(HB));
}
template <uint32_t HA, uint32_t HB>
__device__ __forceinline__ void wgmma_ss_n128_tb(float (&d)[64], uint32_t la, uint32_t lb) {
  asm volatile("{\n.reg .pred p;\n.reg .b64 da, db;\n"
    "mov.b64 da, {%64, %66};\nmov.b64 db, {%65, %67};\n"
    "setp.ne.b32 p, 1, 0;\n"
    "wgmma.mma_async.sync.aligned.m64n128k16.f32.bf16.bf16 "
    "{%0, %1, %2, %3, %4, %5, %6, %7, %8, %9, %10, %11, %12, %13, %14, %15, "
    "%16, %17, %18, %19, %20, %21, %22, %23, %24, %25, %26, %27, %28, %29, %30, %31, "
    "%32, %33, %34, %35, %36, %37, %38, %39, %40, %41, %42, %43, %44, %45, %46, %47, "
    "%48, %49, %50, %51, %52, %53, %54, %55, %56, %57, %58, %59, %60, %61, %62, %63}, "
    "da, db, p, 1, 1, 0, 1;\n}\n"
    : "+f"(d[0]), "+f"(d[1]), "+f"(d[2]), "+f"(d[3]), "+f"(d[4]), "+f"(d[5]), "+f"(d[6]), "+f"(d[7]),
      "+f"(d[8]), "+f"(d[9]), "+f"(d[10]), "+f"(d[11]), "+f"(d[12]), "+f"(d[13]), "+f"(d[14]), "+f"(d[15]),
      "+f"(d[16]), "+f"(d[17]), "+f"(d[18]), "+f"(d[19]), "+f"(d[20]), "+f"(d[21]), "+f"(d[22]), "+f"(d[23]),
      "+f"(d[24]), "+f"(d[25]), "+f"(d[26]), "+f"(d[27]), "+f"(d[28]), "+f"(d[29]), "+f"(d[30]), "+f"(d[31]),
      "+f"(d[32]), "+f"(d[33]), "+f"(d[34]), "+f"(d[35]), "+f"(d[36]), "+f"(d[37]), "+f"(d[38]), "+f"(d[39]),
      "+f"(d[40]), "+f"(d[41]), "+f"(d[42]), "+f"(d[43]), "+f"(d[44]), "+f"(d[45]), "+f"(d[46]), "+f"(d[47]),
      "+f"(d[48]), "+f"(d[49]), "+f"(d[50]), "+f"(d[51]), "+f"(d[52]), "+f"(d[53]), "+f"(d[54]), "+f"(d[55]),
      "+f"(d[56]), "+f"(d[57]), "+f"(d[58]), "+f"(d[59]), "+f"(d[60]), "+f"(d[61]), "+f"(d[62]), "+f"(d[63])
    : "r"(la), "r"(lb), "n"(HA), "n"(HB));
}
template <uint32_t HA, uint32_t HB>
__device__ __forceinline__ void wgmma_ss_n128_tb_z(float (&d)[64], uint32_t la, uint32_t lb) {
  asm volatile("{\n.reg .pred p;\n.reg .b64 da, db;\n"
    "mov.b64 da, {%64, %66};\nmov.b64 db, {%65, %67};\n"
    "setp.ne.b32 p, 0, 0;\n"
    "wgmma.mma_async.sync.aligned.m64n128k16.f32.bf16.bf16 "
    "{%0, %1, %2, %3, %4, %5, %6, %7, %8, %9, %10, %11, %12, %13, %14, %15, "
    "%16, %17, %18, %19, %20, %21, %22, %23, %24, %25, %26, %27, %28, %29, %30, %31, "
    "%32, %33, %34, %35, %36, %37, %38, %39, %40, %41, %42, %43, %44, %45, %46, %47, "
    "%48, %49, %50, %51, %52, %53, %54, %55, %56, %57, %58, %59, %60, %61, %62, %63}, "
    "da, db, p, 1, 1, 0, 1;\n}\n"
    : "=f"(d[0]), "=f"(d[1]), "=f"(d[2]), "=f"(d[3]), "=f"(d[4]), "=f"(d[5]), "=f"(d[6]), "=f"(d[7]),
      "=f"(d[8]), "=f"(d[9]), "=f"(d[10]), "=f"(d[11]), "=f"(d[12]), "=f"(d[13]), "=f"(d[14]), "=f"(d[15]),
      "=f"(d[16]), "=f"(d[17]), "=f"(d[18]), "=f"(d[19]), "=f"(d[20]), "=f"(d[21]), "=f"(d[22]), "=f"(d[23]),
      "=f"(d[24]), "=f"(d[25]), "=f"(d[26]), "=f"(d[27]), "=f"(d[28]), "=f"(d[29]), "=f"(d[30]), "=f"(d[31]),
      "=f"(d[32]), "=f"(d[33]), "=f"(d[34]), "=f"(d[35]), "=f"(d[36]), "=f"(d[37]), "=f"(d[38]), "=f"(d[39]),
      "=f"(d[40]), "=f"(d[41]), "=f"(d[42]), "=f"(d[43]), "=f"(d[44]), "=f"(d[45]), "=f"(d[46]), "=f"(d[47]),
      "=f"(d[48]), "=f"(d[49]), "=f"(d[50]), "=f"(d[51]), "=f"(d[52]), "=f"(d[53]), "=f"(d[54]), "=f"(d[55]),
      "=f"(d[56]), "=f"(d[57]), "=f"(d[58]), "=f"(d[59]), "=f"(d[60]), "=f"(d[61]), "=f"(d[62]), "=f"(d[63])
    : "r"(la), "r"(lb), "n"(HA), "n"(HB));
}
template <uint32_t HA, uint32_t HB>
__device__ __forceinline__ void wgmma_ss_n40_tb_ta(float (&d)[20], uint32_t la, uint32_t lb) {
  asm volatile("{\n.reg .pred p;\n.reg .b64 da, db;\n"
    "mov.b64 da, {%20, %22};\nmov.b64 db, {%21, %23};\n"
    "setp.ne.b32 p, 1, 0;\n"
    "wgmma.mma_async.sync.aligned.m64n40k16.f32.bf16.bf16 "
    "{%0, %1, %2, %3, %4, %5, %6, %7, %8, %9, %10, %11, %12, %13, %14, %15, "
    "%16, %17, %18, %19}, "
    "da, db, p, 1, 1, 1, 1;\n}\n"
    : "+f"(d[0]), "+f"(d[1]), "+f"(d[2]), "+f"(d[3]), "+f"(d[4]), "+f"(d[5]), "+f"(d[6]), "+f"(d[7]),
      "+f"(d[8]), "+f"(d[9]), "+f"(d[10]), "+f"(d[11]), "+f"(d[12]), "+f"(d[13]), "+f"(d[14]), "+f"(d[15]),
      "+f"(d[16]), "+f"(d[17]), "+f"(d[18]), "+f"(d[19])
    : "r"(la), "r"(lb), "n"(HA), "n"(HB));
}
template <uint32_t HA, uint32_t HB>
__device__ __forceinline__ void wgmma_ss_n40_tb_ta_z(float (&d)[20], uint32_t la, uint32_t lb) {
  asm volatile("{\n.reg .pred p;\n.reg .b64 da, db;\n"
    "mov.b64 da, {%20, %22};\nmov.b64 db, {%21, %23};\n"
    "setp.ne.b32 p, 0, 0;\n"
    "wgmma.mma_async.sync.aligned.m64n40k16.f32.bf16.bf16 "
    "{%0, %1, %2, %3, %4, %5, %6, %7, %8, %9, %10, %11, %12, %13, %14, %15, "
    "%16, %17, %18, %19}, "
    "da, db, p, 1, 1, 1, 1;\n}\n"
    : "=f"(d[0]), "=f"(d[1]), "=f"(d[2]), "=f"(d[3]), "=f"(d[4]), "=f"(d[5]), "=f"(d[6]), "=f"(d[7]),
      "=f"(d[8]), "=f"(d[9]), "=f"(d[10]), "=f"(d[11]), "=f"(d[12]), "=f"(d[13]), "=f"(d[14]), "=f"(d[15]),
      "=f"(d[16]), "=f"(d[17]), "=f"(d[18]), "=f"(d[19])
    : "r"(la), "r"(lb), "n"(HA), "n"(HB));
}
template <uint32_t HB>
__device__ __forceinline__ void wgmma_rs_n40_tb(float (&d)[20], uint32_t a0, uint32_t a1, uint32_t a2, uint32_t a3, uint32_t lb) {
  asm volatile("{\n.reg .pred p;\n.reg .b64 db;\n"
    "mov.b64 db, {%24, %25};\n"
    "setp.ne.b32 p, 1, 0;\n"
    "wgmma.mma_async.sync.aligned.m64n40k16.f32.bf16.bf16 "
    "{%0, %1, %2, %3, %4, %5, %6, %7, %8, %9, %10, %11, %12, %13, %14, %15, "
    "%16, %17, %18, %19}, "
    "{%20, %21, %22, %23}, db, p, 1, 1, 1;\n}\n"
    : "+f"(d[0]), "+f"(d[1]), "+f"(d[2]), "+f"(d[3]), "+f"(d[4]), "+f"(d[5]), "+f"(d[6]), "+f"(d[7]),
      "+f"(d[8]), "+f"(d[9]), "+f"(d[10]), "+f"(d[11]), "+f"(d[12]), "+f"(d[13]), "+f"(d[14]), "+f"(d[15]),
      "+f"(d[16]), "+f"(d[17]), "+f"(d[18]), "+f"(d[19])
    : "r"(a0), "r"(a1), "r"(a2), "r"(a3), "r"(lb), "n"(HB));
}
template <uint32_t HB>
__device__ __forceinline__ void wgmma_rs_n40_tb_z(float (&d)[20], uint32_t a0, uint32_t a1, uint32_t a2, uint32_t a3, uint32_t lb) {
  asm volatile("{\n.reg .pred p;\n.reg .b64 db;\n"
    "mov.b64 db, {%24, %25};\n"
    "setp.ne.b32 p, 0, 0;\n"
    "wgmma.mma_async.sync.aligned.m64n40k16.f32.bf16.bf16 "
    "{%0, %1, %2, %3, %4, %5, %6, %7, %8, %9, %10, %11, %12, %13, %14, %15, "
    "%16, %17, %18, %19}, "
    "{%20, %21, %22, %23}, db, p, 1, 1, 1;\n}\n"
    : "=f"(d[0]), "=f"(d[1]), "=f"(d[2]), "=f"(d[3]), "=f"(d[4]), "=f"(d[5]), "=f"(d[6]), "=f"(d[7]),
      "=f"(d[8]), "=f"(d[9]), "=f"(d[10]), "=f"(d[11]), "=f"(d[12]), "=f"(d[13]), "=f"(d[14]), "=f"(d[15]),
      "=f"(d[16]), "=f"(d[17]), "=f"(d[18]), "=f"(d[19])
    : "r"(a0), "r"(a1), "r"(a2), "r"(a3), "r"(lb), "n"(HB));
}
template <uint32_t HB>
__device__ __forceinline__ void wgmma_rs_n32(float (&d)[16], uint32_t a0, uint32_t a1, uint32_t a2, uint32_t a3, uint32_t lb) {
  asm volatile("{\n.reg .pred p;\n.reg .b64 db;\n"
    "mov.b64 db, {%20, %21};\n"
    "setp.ne.b32 p, 1, 0;\n"
    "wgmma.mma_async.sync.aligned.m64n32k16.f32.bf16.bf16 "
    "{%0, %1, %2, %3, %4, %5, %6, %7, %8, %9, %10, %11, %12, %13, %14, %15}, "
    "{%16, %17, %18, %19}, db, p, 1, 1, 0;\n}\n"
    : "+f"(d[0]), "+f"(d[1]), "+f"(d[2]), "+f"(d[3]), "+f"(d[4]), "+f"(d[5]), "+f"(d[6]), "+f"(d[7]),
      "+f"(d[8]), "+f"(d[9]), "+f"(d[10]), "+f"(d[11]), "+f"(d[12]), "+f"(d[13]), "+f"(d[14]), "+f"(d[15])
    : "r"(a0), "r"(a1), "r"(a2), "r"(a3), "r"(lb), "n"(HB));
}
template <uint32_t HB>
__device__ __forceinline__ void wgmma_rs_n32_z(float (&d)[16], uint32_t a0, uint32_t a1, uint32_t a2, uint32_t a3, uint32_t lb) {
  asm volatile("{\n.reg .pred p;\n.reg .b64 db;\n"
    "mov.b64 db, {%20, %21};\n"
    "setp.ne.b32 p, 0, 0;\n"
    "wgmma.mma_async.sync.aligned.m64n32k16.f32.bf16.bf16 "
    "{%0, %1, %2, %3, %4, %5, %6, %7, %8, %9, %10, %11, %12, %13, %14, %15}, "
    "{%16, %17, %18, %19}, db, p, 1, 1, 0;\n}\n"
    : "=f"(d[0]), "=f"(d[1]), "=f"(d[2]), "=f"(d[3]), "=f"(d[4]), "=f"(d[5]), "=f"(d[6]), "=f"(d[7]),
      "=f"(d[8]), "=f"(d[9]), "=f"(d[10]), "=f"(d[11]), "=f"(d[12]), "=f"(d[13]), "=f"(d[14]), "=f"(d[15])
    : "r"(a0), "r"(a1), "r"(a2), "r"(a3), "r"(lb), "n"(HB));
}
template <uint32_t HB>
__device__ __forceinline__ void wgmma_rs_n64(float (&d)[32], uint32_t a0, uint32_t a1, uint32_t a2, uint32_t a3, uint32_t lb) {
  asm volatile("{\n.reg .pred p;\n.reg .b64 db;\n"
    "mov.b64 db, {%36, %37};\n"
    "setp.ne.b32 p, 1, 0;\n"
    "wgmma.mma_async.sync.aligned.m64n64k16.f32.bf16.bf16 "
    "{%0, %1, %2, %3, %4, %5, %6, %7, %8, %9, %10, %11, %12, %13, %14, %15, "
    "%16, %17, %18, %19, %20, %21, %22, %23, %24, %25, %26, %27, %28, %29, %30, %31}, "
    "{%32, %33, %34, %35}, db, p, 1, 1, 0;\n}\n"
    : "+f"(d[0]), "+f"(d[1]), "+f"(d[2]), "+f"(d[3]), "+f"(d[4]), "+f"(d[5]), "+f"(d[6]), "+f"(d[7]),
      "+f"(d[8]), "+f"(d[9]), "+f"(d[10]), "+f"(d[11]), "+f"(d[12]), "+f"(d[13]), "+f"(d[14]), "+f"(d[15]),
      "+f"(d[16]), "+f"(d[17]), "+f"(d[18]), "+f"(d[19]), "+f"(d[20]), "+f"(d[21]), "+f"(d[22]), "+f"(d[23]),
      "+f"(d[24]), "+f"(d[25]), "+f"(d[26]), "+f"(d[27]), "+f"(d[28]), "+f"(d[29]), "+f"(d[30]), "+f"(d[31])
    : "r"(a0), "r"(a1), "r"(a2), "r"(a3), "r"(lb), "n"(HB));
}
template <uint32_t HB>
__device__ __forceinline__ void wgmma_rs_n64_z(float (&d)[32], uint32_t a0, uint32_t a1, uint32_t a2, uint32_t a3, uint32_t lb) {
  asm volatile("{\n.reg .pred p;\n.reg .b64 db;\n"
    "mov.b64 db, {%36, %37};\n"
    "setp.ne.b32 p, 0, 0;\n"
    "wgmma.mma_async.sync.aligned.m64n64k16.f32.bf16.bf16 "
    "{%0, %1, %2, %3, %4, %5, %6, %7, %8, %9, %10, %11, %12, %13, %14, %15, "
    "%16, %17, %18, %19, %20, %21, %22, %23, %24, %25, %26, %27, %28, %29, %30, %31}, "
    "{%32, %33, %34, %35}, db, p, 1, 1, 0;\n}\n"
    : "=f"(d[0]), "=f"(d[1]), "=f"(d[2]), "=f"(d[3]), "=f"(d[4]), "=f"(d[5]), "=f"(d[6]), "=f"(d[7]),
      "=f"(d[8]), "=f"(d[9]), "=f"(d[10]), "=f"(d[11]), "=f"(d[12]), "=f"(d[13]), "=f"(d[14]), "=f"(d[15]),
      "=f"(d[16]), "=f"(d[17]), "=f"(d[18]), "=f"(d[19]), "=f"(d[20]), "=f"(d[21]), "=f"(d[22]), "=f"(d[23]),
      "=f"(d[24]), "=f"(d[25]), "=f"(d[26]), "=f"(d[27]), "=f"(d[28]), "=f"(d[29]), "=f"(d[30]), "=f"(d[31])
    : "r"(a0), "r"(a1), "r"(a2), "r"(a3), "r"(lb), "n"(HB));
}
#include <type_traits>

constexpr int SEQ = 2048, DM = 1024, NH = 32;
constexpr int NPAIR = 66;

constexpr float QSCALE = 0.17677669529663687f * 1.4426950408889634f;
constexpr float LOG2E = 1.4426950408889634f;

__device__ __align__(1024) uint8_t g_qkv[3 * NH * SEQ * 64];
__device__ __align__(1024) uint8_t g_o[2 * 16 * NH * 8192];
__device__ __align__(16) float g_stats[3 * NH * 128];
__device__ __align__(128) float g_kv[NH * 32 * 40];
__device__ __align__(128) uint32_t g_kvb[NH * 640];

enum { C_AKV = 0, C_ATT = 16, C_BKV = 32, C_KVB = 48, C_AQ = 64, C_BQ = 128, C_NUM = 136 };
__device__ uint32_t g_cnt[C_NUM * 8];
__device__ uint32_t g_epoch, g_exit;

enum { T_AKV = 0, T_AQ = 1, T_BKV = 2, T_BQ = 3, T_BOUT = 4, T_AOUT = 5, T_AOUT2 = 6, T_NONE = 7 };
constexpr int MAXT = 10;

struct MegaParams {
  CUtensorMap x[2];
  CUtensorMap wkv[2];
  CUtensorMap wblk[4];
  CUtensorMap out;
  const uint8_t* xa; const uint8_t* wa;
  uint16_t gt[NPAIR][MAXT];
  uint8_t at[NPAIR][4];
  uint8_t na[NPAIR];
};

constexpr int G_STAGES = 4;
constexpr int G_STAGE = 32768;
constexpr int S_STG = G_STAGES * G_STAGE;
constexpr int KV_STAGES = 3;
constexpr int S_KV = S_STG + 32768;
constexpr int S_OST = S_KV + KV_STAGES * 16384;
constexpr int S_ONES = S_OST + 8192;
constexpr int S_STAT = S_ONES + 1024;
constexpr int S_BAR = S_STAT + 192;
constexpr int G_STAGES0 = 6;
constexpr int B_GFULL = S_BAR, B_GEMPTY = B_GFULL + 8 * G_STAGES0;
constexpr int B_T0DONE = B_GEMPTY + 8 * G_STAGES0, B_LFREE = B_T0DONE + 8, B_ADONE = B_LFREE + 8;
constexpr int B_KFULL = B_ADONE + 8, B_KEMPTY = B_KFULL + 8 * KV_STAGES;
constexpr int B_SFULL = B_KEMPTY + 8 * KV_STAGES, B_SFREE = B_SFULL + 8;
constexpr int B_OFULL = B_SFREE + 8, B_OFREE = B_OFULL + 16;
constexpr int B_RDY = B_OFREE + 16, B_VERD = B_RDY + 8;
constexpr int S_FAST = B_VERD + 8;
constexpr int S_EPOCH = S_FAST + 32;
constexpr int MEGA_SMEM = S_EPOCH + 16 + 1024;
static_assert(MEGA_SMEM <= 232448, "shared memory");

constexpr uint32_t HI_NOSW_128 = (128 >> 4);

#ifndef M_AREGS
#define M_AREGS 128
#endif
#ifndef M_GREGS
#define M_GREGS 184
#endif
#ifndef M_PREGS
#define M_PREGS 72
#endif
#ifndef M_GSPLIT
#define M_GSPLIT 0
#endif
#ifndef M_GWAIT
#define M_GWAIT 0
#endif

template <int I> using IC = std::integral_constant<int, I>;
template <int N, class F, int I = 0> __device__ __forceinline__ void static_for(F&& f) {
  if constexpr (I < N) { f(IC<I>{}); static_for<N, F, I + 1>(static_cast<F&&>(f)); }
}

#define TIMR(role, i)
#define TIMW(cond, role, i)

__device__ __forceinline__ uint32_t ld_relaxed(const uint32_t* p) {
  uint32_t v;
  asm volatile("ld.relaxed.gpu.global.u32 %0, [%1];" : "=r"(v) : "l"(p) : "memory");
  return v;
}
__device__ __forceinline__ void fence_proxy_async_all() { asm volatile("fence.proxy.async;" ::: "memory"); }
#ifndef M_FENCE
#define M_FENCE 0
#endif
#ifndef M_SLEEP
#define M_SLEEP 40
#endif
__device__ __forceinline__ void cnt_wait(int c, uint32_t epoch, uint32_t target) {
  const uint32_t* p = g_cnt + c * 8;
  const uint32_t want = epoch * target + target;
  uint32_t spins = 0;
  while ((int32_t)(ld_relaxed(p) - want) < 0) {
    __nanosleep(M_SLEEP);
    if (++spins > (1u << 22)) __trap();
  }
  if (M_FENCE) { asm volatile("fence.acq_rel.gpu;" ::: "memory"); fence_proxy_async_all(); }
}
__device__ __forceinline__ void cnt_wait2(int c0, uint32_t t0, int c1, uint32_t t1, uint32_t epoch) {
  const uint32_t *p0 = g_cnt + c0 * 8, *p1 = g_cnt + c1 * 8;
  const uint32_t w0 = epoch * t0 + t0, w1 = epoch * t1 + t1;
  uint32_t spins = 0;
  while (true) {
    const uint32_t a = ld_relaxed(p0), b = ld_relaxed(p1);
    if ((int32_t)(a - w0) >= 0 && (int32_t)(b - w1) >= 0) break;
    __nanosleep(M_SLEEP);
    if (++spins > (1u << 22)) __trap();
  }
  if (M_FENCE) { asm volatile("fence.acq_rel.gpu;" ::: "memory"); fence_proxy_async_all(); }
}
__device__ __forceinline__ uint32_t cnt_add(int c) {
  uint32_t old;
  if (M_FENCE) { fence_proxy_async_all(); asm volatile("fence.acq_rel.gpu;" ::: "memory"); }
  asm volatile("atom.add.relaxed.gpu.global.u32 %0, [%1], 1;" : "=r"(old) : "l"(g_cnt + c * 8) : "memory");
  return old;
}
__device__ __forceinline__ void cnt_red(int c, uint32_t v) {
  if (M_FENCE) { fence_proxy_async_all(); asm volatile("fence.acq_rel.gpu;" ::: "memory"); }
  asm volatile("red.add.relaxed.gpu.global.u32 [%0], %1;" ::"l"(g_cnt + c * 8), "r"(v) : "memory");
}

struct Tile { int type, idx, mp; };
__device__ __forceinline__ Tile decode_tile(uint32_t e) { return Tile{(int)(e & 7), (int)((e >> 3) & 15), (int)(e >> 7)}; }

__device__ __forceinline__ float phi_fn(float t) {
  const float e = ex2_approx(t * LOG2E);
  const float y = t > 0.f ? t + 1.f : e;
  return y + 1e-6f;
}
__device__ __forceinline__ void bulk_load_1d(uint32_t dst, const void* src, uint32_t bytes, uint32_t bar) {
  asm volatile("cp.async.bulk.shared::cluster.global.mbarrier::complete_tx::bytes [%0], [%1], %2, [%3];"
               ::"r"(dst), "l"(src), "r"(bytes), "r"(bar) : "memory");
}
__device__ __forceinline__ void bulk_load_1d_mc(uint32_t dst, const void* src, uint32_t bytes, uint32_t bar, uint16_t mask) {
  asm volatile("cp.async.bulk.shared::cluster.global.mbarrier::complete_tx::bytes.multicast::cluster [%0], [%1], %2, [%3], %4;"
               ::"r"(dst), "l"(src), "r"(bytes), "r"(bar), "h"(mask) : "memory");
}
__device__ __forceinline__ void bulk_store_1d(void* dst, uint32_t src, uint32_t bytes) {
  asm volatile("cp.async.bulk.global.shared::cta.bulk_group [%0], [%1], %2;" ::"l"(dst), "r"(src), "r"(bytes) : "memory");
}
template <int N> struct Ring {
  int slot; uint32_t phase;
  __device__ __forceinline__ void advance() { if (++slot == N) { slot = 0; phase ^= 1; } }
  __device__ __forceinline__ Ring next() const { Ring r = *this; r.advance(); return r; }
};
__device__ __forceinline__ void tma_reduce_add_2d(const CUtensorMap* m, uint32_t src, int c0, int c1) {
  asm volatile("cp.reduce.async.bulk.tensor.2d.global.shared::cta.add.tile.bulk_group [%0, {%2, %3}], [%1];"
               ::"l"(m), "r"(src), "r"(c0), "r"(c1) : "memory");
}
__device__ __forceinline__ void bulk_reduce_add_f32(void* dst, uint32_t src, uint32_t bytes) {
  asm volatile("cp.reduce.async.bulk.global.shared::cta.bulk_group.add.f32 [%0], [%1], %2;" ::"l"(dst), "r"(src), "r"(bytes) : "memory");
}

#define KV_MC 1
#define ATT_SB 32
#define ATT_EARLY 4
__device__ __forceinline__ float ex2_volatile(float x) {
  float y;
  asm volatile("ex2.approx.ftz.f32 %0, %1;" : "=f"(y) : "f"(x));
  return y;
}
using KvRing = Ring<KV_STAGES>;
template <int SB> struct QKmma;
template <> struct QKmma<32> {
  static __device__ __forceinline__ void run(float (&s)[16], const uint32_t (&q)[8], uint32_t d) {
    wgmma_rs_n32_z<HI_SW64_512>(s, q[0], q[1], q[2], q[3], d);
    wgmma_rs_n32<HI_SW64_512>(s, q[4], q[5], q[6], q[7], d + 2);
  }
};
template <> struct QKmma<64> {
  static __device__ __forceinline__ void run(float (&s)[32], const uint32_t (&q)[8], uint32_t d) {
    wgmma_rs_n64_z<HI_SW64_512>(s, q[0], q[1], q[2], q[3], d);
    wgmma_rs_n64<HI_SW64_512>(s, q[4], q[5], q[6], q[7], d + 2);
  }
};
template <class Release, class Tail>
__device__ __forceinline__ void attn_item_fast(float (&o)[20], const uint32_t (&q)[8], uint32_t sb, KvRing& r, Release&& release, Tail&& tail_hook) {
  constexpr int SB = ATT_SB, U = 128 / SB, NP = SB / 4;
  constexpr uint32_t SOFF = SB * 4;
  float S[2][SB / 2];
  uint32_t P[2][NP];
  const uint32_t kd0 = desc_lo(sb + S_KV, 16), vd0 = desc_lo(sb + S_KV + 8192, (uint32_t)(S_ONES - S_KV - 8192));
  auto pv = [&](const uint32_t (&p)[NP], uint32_t vo) {
    const uint32_t d0 = vd0 + vo - (vo << 16);
#pragma unroll
    for (int k = 0; k < SB / 16; k++)
      wgmma_rs_n40_tb<HI_SW64_512>(o, p[4 * k], p[4 * k + 1], p[4 * k + 2], p[4 * k + 3], d0 + 64u * k - ((64u * k) << 16));
  };
  wg_fence();
  QKmma<SB>::run(S[0], q, kd0 + (uint32_t)r.slot * 1024u);
  wg_commit();
  wg_commit();
  int prev_slot = -1;
  auto step = [&](auto uc, auto issue_c, auto first_c, const KvRing& nx) {
    constexpr int u = decltype(uc)::value;
    constexpr bool issue = decltype(issue_c)::value, first = decltype(first_c)::value;
    const uint32_t a0 = (uint32_t)r.slot * 1024u;
    if constexpr (issue) {
      if constexpr (u == U - 1) mbar_wait(sb + B_KFULL + 8 * nx.slot, nx.phase);
      wg_fence();
      QKmma<SB>::run(S[(u + 1) & 1], q, kd0 + (u == U - 1 ? (uint32_t)nx.slot * 1024u : a0 + (u + 1) * SOFF));
    }
    wg_commit();
    wg_wait<1>();
    fence_regs(S[u & 1]);
    if constexpr (u == 1) { if (prev_slot >= 0) release(prev_slot); }
    float e[ATT_EARLY];
#pragma unroll
    for (int i = 0; i < ATT_EARLY; i++) e[i] = ex2_volatile(S[u & 1][i]);
    if constexpr (!first) {
      wg_fence();
      pv(P[(u + 1) & 1], u == 0 ? (uint32_t)prev_slot * 1024u + (U - 1) * SOFF : a0 + (u - 1) * SOFF);
    }
    wg_commit();
#pragma unroll
    for (int i = 0; i < NP; i++) {
      const float x = 2 * i < ATT_EARLY ? e[2 * i < ATT_EARLY ? 2 * i : 0] : ex2_approx(S[u & 1][2 * i]);
      const float y = 2 * i + 1 < ATT_EARLY ? e[2 * i + 1 < ATT_EARLY ? 2 * i + 1 : 0] : ex2_approx(S[u & 1][2 * i + 1]);
      P[u & 1][i] = pack_bf16(x, y);
    }
  };
  {
    const KvRing nx = r.next();
    static_for<U>([&](auto uc) {
      constexpr bool first = decltype(uc)::value == 0;
      step(uc, std::true_type{}, std::integral_constant<bool, first>{}, nx);
    });
    prev_slot = r.slot;
    r = nx;
  }
#pragma unroll 1
  for (int st = 1; st < 15; st++) {
    const KvRing nx = r.next();
    static_for<U>([&](auto uc) { step(uc, std::true_type{}, std::false_type{}, nx); });
    prev_slot = r.slot;
    r = nx;
  }
  tail_hook();
  static_for<U>([&](auto uc) {
    constexpr bool more = decltype(uc)::value != U - 1;
    step(uc, std::integral_constant<bool, more>{}, std::false_type{}, r);
  });
  wg_fence();
  pv(P[(U - 1) & 1], (uint32_t)r.slot * 1024u + (U - 1) * SOFF);
  wg_commit();
  wg_wait<0>();
  release(r.slot);
  r.advance();
  fence_regs(o);
}

template <class Release, class Tail>
__device__ __forceinline__ void attn_item_safe(float (&o)[20], const uint32_t (&q)[8], uint32_t sb, KvRing& r, Release&& release, Tail&& tail_hook) {
  float m0 = -INFINITY, m1 = -INFINITY;
#pragma unroll 1
  for (int j = 0; j < 32; j++) {
    if (j == 30) tail_hook();
    if ((j & 1) == 0) mbar_wait(sb + B_KFULL + 8 * r.slot, r.phase);
    const uint32_t cur = sb + S_KV + r.slot * 16384 + (j & 1) * 4096;
    float s[32];
    uint32_t p[16];
    wg_fence();
    wgmma_rs_n64_z<HI_SW64_512>(s, q[0], q[1], q[2], q[3], desc_lo(cur, 16));
    wgmma_rs_n64<HI_SW64_512>(s, q[4], q[5], q[6], q[7], desc_lo(cur, 16) + 2);
    wg_commit();
    wg_wait<0>();
    fence_regs(s);
    float n0r = m0, n1r = m1;
#pragma unroll
    for (int i = 0; i < 8; i++) {
      n0r = fmaxf(n0r, fmaxf(s[4 * i], s[4 * i + 1]));
      n1r = fmaxf(n1r, fmaxf(s[4 * i + 2], s[4 * i + 3]));
    }
    n0r = fmaxf(n0r, __shfl_xor_sync(0xffffffffu, n0r, 1));
    n1r = fmaxf(n1r, __shfl_xor_sync(0xffffffffu, n1r, 1));
    n0r = fmaxf(n0r, __shfl_xor_sync(0xffffffffu, n0r, 2));
    n1r = fmaxf(n1r, __shfl_xor_sync(0xffffffffu, n1r, 2));
    const float c0 = exp2f(m0 - n0r), c1 = exp2f(m1 - n1r);
    m0 = n0r; m1 = n1r;
#pragma unroll
    for (int i = 0; i < 5; i++) { o[4 * i] *= c0; o[4 * i + 1] *= c0; o[4 * i + 2] *= c1; o[4 * i + 3] *= c1; }
#pragma unroll
    for (int i = 0; i < 8; i++) {
      p[2 * i] = pack_bf16(ex2_approx(s[4 * i] - m0), ex2_approx(s[4 * i + 1] - m0));
      p[2 * i + 1] = pack_bf16(ex2_approx(s[4 * i + 2] - m1), ex2_approx(s[4 * i + 3] - m1));
    }
    fence_regs(o);
    wg_fence();
    const uint32_t v = cur + 8192;
    const uint32_t d0 = desc_lo(v, sb + S_ONES - v);
#pragma unroll
    for (int k = 0; k < 4; k++)
      wgmma_rs_n40_tb<HI_SW64_512>(o, p[4 * k], p[4 * k + 1], p[4 * k + 2], p[4 * k + 3], d0 + 64u * k - ((64u * k) << 16));
    wg_commit();
    wg_wait<0>();
    fence_regs(o);
    if (j & 1) { release(r.slot); r.advance(); }
  }
}

struct GPipe {
  int slot; uint32_t mask;
  __device__ __forceinline__ uint32_t parity() const { return (mask >> slot) & 1u; }
  __device__ __forceinline__ void advance(int n) { mask ^= 1u << slot; slot = slot + 1 >= n ? 0 : slot + 1; }
};
__device__ __forceinline__ uint32_t g_slot_off(int slot) {
  return slot < G_STAGES ? (uint32_t)slot * G_STAGE : (slot == G_STAGES ? (uint32_t)S_STG : (uint32_t)S_KV);
}
template <bool AIMG, bool FIRST>
__device__ __forceinline__ void gemm_mma1(float (&a)[64], uint32_t da, uint32_t db) {
  constexpr uint32_t HA = AIMG ? HI_SW64_512 : HI_SW128_1024;
  if constexpr (FIRST) wgmma_ss_n128_tb_z<HA, HI_SW128_1024>(a, da, db); else wgmma_ss_n128_tb<HA, HI_SW128_1024>(a, da, db);
}
template <bool AIMG, int GRP, int WAIT, int NST, int KT0, int KT1, bool INIT = (KT0 == 0)>
__device__ __forceinline__ void gemm_stages(float (&a0)[64], float (&a1)[64], uint32_t sb, GPipe& r, int tid, uint32_t rank) {
  constexpr uint32_t MH = AIMG ? 256 : 512;
  const uint32_t da0 = desc_lo(sb, 16), db0 = desc_lo(sb + 16384, 4096);
  int prev = r.slot;
  auto release = [&](int s) { mbar_arrive_pair(sb + B_GEMPTY + 8 * s, tid); };
  auto stage = [&](auto first_c, auto head_c) {
    constexpr bool first = decltype(first_c)::value;
    constexpr bool head = decltype(head_c)::value;
    mbar_wait(sb + B_GFULL + 8 * r.slot, r.parity());
    const uint32_t off = (NST == G_STAGES ? (uint32_t)r.slot * G_STAGE : g_slot_off(r.slot)) >> 4;
    static_for<4>([&](auto kc) {
      constexpr int ks = decltype(kc)::value;
      constexpr uint32_t oa = AIMG ? (ks >> 1) * 512 + (ks & 1) * 2 : ks * 2;
      constexpr uint32_t ob = (ks >> 1) * 512 + (ks & 1) * 128;
      if constexpr (ks % GRP == 0) wg_fence();
      gemm_mma1<AIMG, first && ks == 0>(a0, da0 + off + oa, db0 + off + ob);
      gemm_mma1<AIMG, first && ks == 0>(a1, da0 + off + oa + MH, db0 + off + ob);
      if constexpr (ks % GRP == GRP - 1) {
        wg_commit();
        wg_wait<WAIT>();
        if constexpr (WAIT == 1 && ks == GRP - 1 && !head) release(prev);
      }
    });
    if constexpr (WAIT == 0) release(r.slot);
    prev = r.slot;
    r.advance(NST);
  };
  stage(std::integral_constant<bool, INIT>{}, std::true_type{});
#pragma unroll 1
  for (int kt = KT0 + 1; kt < KT1; kt++) stage(std::false_type{}, std::false_type{});
  if constexpr (WAIT == 1) { wg_wait<0>(); release(prev); }
  __syncwarp();
}

__device__ __forceinline__ void stage_slot(uint32_t stg, int s, int m, int wq, int lane, const uint32_t (&p)[8]) {
  const int row = m * 64 + wq * 16 + (lane & 7) + ((lane >> 3) & 1) * 8;
  const uint32_t a = stg + s * 8192 + row * 64;
  const int sw = (row >> 1) & 3, ch = lane >> 4;
  stmatrix_x4(a + ((ch ^ sw) << 4), p[0], p[1], p[2], p[3]);
  stmatrix_x4(a + (((ch + 2) ^ sw) << 4), p[4], p[5], p[6], p[7]);
}
__device__ __forceinline__ void stage_slot_box(uint32_t stg, int s, int m, int wq, int lane, const uint32_t (&p)[8]) {
  const int row = m * 64 + wq * 16 + (lane & 7) + ((lane >> 3) & 1) * 8;
  const uint32_t a = stg + (s >> 1) * 16384 + row * 128;
  const int sw = row & 7, ch = (s & 1) * 4 + (lane >> 4);
  stmatrix_x4(a + ((ch ^ sw) << 4), p[0], p[1], p[2], p[3]);
  stmatrix_x4(a + (((ch + 2) ^ sw) << 4), p[4], p[5], p[6], p[7]);
}

#define BQ_BATCH 2
#ifndef M_HOLD
#define M_HOLD -1
#endif
#ifndef M_GRP
#define M_GRP 1
#endif
#ifndef M_WAIT
#define M_WAIT 0
#endif
#ifndef M_GRPB
#define M_GRPB M_GRP
#endif
#ifndef M_WAITB
#define M_WAITB M_WAIT
#endif
#ifndef M_GRPO
#define M_GRPO 1
#endif
#ifndef M_WAITO
#define M_WAITO 1
#endif
#ifndef M_GRPA
#define M_GRPA 1
#endif
#ifndef M_WAITA
#define M_WAITA 1
#endif
#ifndef M_GRP0
#define M_GRP0 1
#endif
#ifndef M_WAIT0
#define M_WAIT0 1
#endif

__device__ __forceinline__ void tile_n128(const Tile& t, int i, uint32_t sb, uint8_t* smem, GPipe& r, int warp, int lane, uint32_t rank) {
  const int wq = warp & 3, tid = threadIdx.x & 127;
  const int qd = lane & 3, r8 = lane >> 2;
  const uint32_t stg = sb + S_STG;
  float a0[64], a1[64];
  if (i == 0) {
    gemm_stages<false, M_GRP0, M_WAIT0, G_STAGES0, 0, 16>(a0, a1, sb, r, tid, rank);
    r.slot = 0;
    mbar_arrive_pair(sb + B_T0DONE, tid);
  } else if (t.type == T_AOUT) {
    gemm_stages<true, M_GRPO, M_WAITO, G_STAGES, 0, 8>(a0, a1, sb, r, tid, rank);
    if (t.mp < 4) gemm_stages<true, M_GRPO, M_WAITO, G_STAGES, 8, 16>(a0, a1, sb, r, tid, rank);
    else gemm_stages<true, M_GRP0, M_WAIT0, G_STAGES0, 8, 16>(a0, a1, sb, r, tid, rank);
  } else if (t.type == T_AOUT2) {
    gemm_stages<true, M_GRP0, M_WAIT0, G_STAGES0, 8, 16, true>(a0, a1, sb, r, tid, rank);
  } else if (t.type == T_BOUT) {
    gemm_stages<true, M_GRPO, M_WAITO, G_STAGES, 0, 16>(a0, a1, sb, r, tid, rank);
  } else if (t.type <= T_AQ) {
    gemm_stages<false, M_GRP, M_WAIT, G_STAGES, 0, 16>(a0, a1, sb, r, tid, rank);
  } else {
    gemm_stages<false, M_GRPB, M_WAITB, G_STAGES, 0, 16>(a0, a1, sb, r, tid, rank);
  }
  fence_regs(a0); fence_regs(a1);
  TIMW(tid == 0, 0, 3 * i + 1);
  if (i > 0) mbar_wait(sb + B_SFREE, (i - 1) & 1);
  if (t.type <= T_AQ) {
    const float sc = t.type == T_AQ ? QSCALE : 1.f;
    float* stat = reinterpret_cast<float*>(smem + S_STAT);
    static_for<4>([&](auto sc_) {
      constexpr int s = decltype(sc_)::value;
      static_for<2>([&](auto mc) {
        constexpr int m = decltype(mc)::value;
        float (&a)[64] = m == 0 ? a0 : a1;
        float s0 = 0.f, s1 = 0.f;
        uint32_t p[8];
#pragma unroll
        for (int j = 0; j < 4; j++) {
          const int b = (s * 4 + j) * 4;
          const float x0 = a[b] * sc, x1 = a[b + 1] * sc, x2 = a[b + 2] * sc, x3 = a[b + 3] * sc;
          s0 = fmaf(x0, x0, s0); s0 = fmaf(x1, x1, s0);
          s1 = fmaf(x2, x2, s1); s1 = fmaf(x3, x3, s1);
          p[2 * j] = pack_bf16(x0, x1);
          p[2 * j + 1] = pack_bf16(x2, x3);
        }
        stage_slot(stg, s, m, wq, lane, p);
        s0 += __shfl_xor_sync(0xffffffffu, s0, 1);
        s1 += __shfl_xor_sync(0xffffffffu, s1, 1);
        s0 += __shfl_xor_sync(0xffffffffu, s0, 2);
        s1 += __shfl_xor_sync(0xffffffffu, s1, 2);
        const uint32_t mx = __reduce_max_sync(0xffffffffu, max(__float_as_uint(s0), __float_as_uint(s1)));
        if (lane == 0) stat[s * 8 + m * 4 + wq] = __uint_as_float(mx);
        __syncwarp();
      });
    });
  } else
  if (t.type == T_BKV) {
    static_for<4>([&](auto sc_) {
      constexpr int s = decltype(sc_)::value;
      static_for<2>([&](auto mc) {
        constexpr int m = decltype(mc)::value;
        float (&a)[64] = m == 0 ? a0 : a1;
        uint32_t p[8];
#pragma unroll
        for (int j = 0; j < 4; j++) {
          const int b = (s * 4 + j) * 4;
          float x0 = a[b], x1 = a[b + 1], x2 = a[b + 2], x3 = a[b + 3];
          if constexpr (s < 2) { x0 = phi_fn(x0); x1 = phi_fn(x1); x2 = phi_fn(x2); x3 = phi_fn(x3); }
          p[2 * j] = pack_bf16(x0, x1);
          p[2 * j + 1] = pack_bf16(x2, x3);
        }
        stage_slot(stg, s, m, wq, lane, p);
      });
    });
    fence_proxy_async_smem();
    named_bar_sync(1, 128);
    float d[2][20];
    wg_fence();
    static_for<2>([&](auto hc) {
      constexpr int hh = decltype(hc)::value;
      const uint32_t tb = stg + (2 + hh) * 8192;
      const uint32_t la = desc_lo(stg, 8192), lb = desc_lo(tb, sb + S_ONES - tb);
      wgmma_ss_n40_tb_ta_z<HI_SW64_512, HI_SW64_512>(d[hh], la, lb);
#pragma unroll
      for (int k = 1; k < 8; k++)
        wgmma_ss_n40_tb_ta<HI_SW64_512, HI_SW64_512>(d[hh], la + 64u * k, lb + 64u * k - ((64u * k) << 16));
    });
    wg_commit();
    wg_wait<0>();
    named_bar_sync(1, 128);
    fence_regs(d[0]); fence_regs(d[1]);
    {
      const int hh = wq >> 1;
      float* dst = reinterpret_cast<float*>(smem + S_STG + hh * 8192) + ((wq & 1) * 16 + r8) * 40 + 2 * qd;
#pragma unroll
      for (int j = 0; j < 5; j++) {
        *reinterpret_cast<float2*>(dst + 8 * j) = hh ? make_float2(d[1][4 * j], d[1][4 * j + 1]) : make_float2(d[0][4 * j], d[0][4 * j + 1]);
        *reinterpret_cast<float2*>(dst + 8 * 40 + 8 * j) = hh ? make_float2(d[1][4 * j + 2], d[1][4 * j + 3]) : make_float2(d[0][4 * j + 2], d[0][4 * j + 3]);
      }
    }
  } else if (t.type == T_BQ) {
    uint32_t pq[2][4][8];
    static_for<4>([&](auto sc_) {
      constexpr int s = decltype(sc_)::value;
      static_for<2>([&](auto mc) {
        constexpr int m = decltype(mc)::value;
        float (&a)[64] = m == 0 ? a0 : a1;
#pragma unroll
        for (int j = 0; j < 4; j++) {
          const int b = (s * 4 + j) * 4;
          pq[m][s][2 * j] = pack_bf16(phi_fn(a[b]), phi_fn(a[b + 1]));
          pq[m][s][2 * j + 1] = pack_bf16(phi_fn(a[b + 2]), phi_fn(a[b + 3]));
        }
      });
    });
    mbar_wait(sb + B_GFULL + 8 * r.slot, r.parity());
    const uint32_t kvd = desc_lo(sb + r.slot * G_STAGE, 640);
    static_for<4 / BQ_BATCH>([&](auto pc) {
      constexpr int sp = decltype(pc)::value;
      float d[BQ_BATCH][2][20];
      wg_fence();
      static_for<BQ_BATCH>([&](auto sc_) {
        constexpr int ss = decltype(sc_)::value, s = BQ_BATCH * sp + ss;
        static_for<2>([&](auto mc) {
          constexpr int m = decltype(mc)::value;
          wgmma_rs_n40_tb_z<HI_NOSW_128>(d[ss][m], pq[m][s][0], pq[m][s][1], pq[m][s][2], pq[m][s][3], kvd + s * 160);
          wgmma_rs_n40_tb<HI_NOSW_128>(d[ss][m], pq[m][s][4], pq[m][s][5], pq[m][s][6], pq[m][s][7], kvd + s * 160 + 80);
        });
      });
      wg_commit();
      wg_wait<0>();
      static_for<BQ_BATCH>([&](auto sc_) {
        constexpr int ss = decltype(sc_)::value, s = BQ_BATCH * sp + ss;
        static_for<2>([&](auto mc) {
          constexpr int m = decltype(mc)::value;
          fence_regs(d[ss][m]);
          const float i0 = rcp_approx(d[ss][m][16] + 1e-6f), i1 = rcp_approx(d[ss][m][18] + 1e-6f);
          uint32_t p[8];
#pragma unroll
          for (int j = 0; j < 4; j++) {
            p[2 * j] = pack_bf16(d[ss][m][4 * j] * i0, d[ss][m][4 * j + 1] * i0);
            p[2 * j + 1] = pack_bf16(d[ss][m][4 * j + 2] * i1, d[ss][m][4 * j + 3] * i1);
          }
          stage_slot(stg, s, m, wq, lane, p);
        });
      });
    });
    mbar_arrive_pair(sb + B_GEMPTY + 8 * r.slot, tid);
    r.advance(G_STAGES);
  } else {
    static_for<4>([&](auto sc_) {
      constexpr int s = decltype(sc_)::value;
      static_for<2>([&](auto mc) {
        constexpr int m = decltype(mc)::value;
        float (&a)[64] = m == 0 ? a0 : a1;
        uint32_t p[8];
#pragma unroll
        for (int j = 0; j < 4; j++) {
          const int b = (s * 4 + j) * 4;
          p[2 * j] = pack_bf16(a[b], a[b + 1]);
          p[2 * j + 1] = pack_bf16(a[b + 2], a[b + 3]);
        }
        stage_slot_box(stg, s, m, wq, lane, p);
      });
    });
  }
}

#define HWAIT mbar_wait_long
__global__ void __cluster_dims__(2, 1, 1) __launch_bounds__(512, 1) mega_kernel(const __grid_constant__ MegaParams prm) {
  extern __shared__ uint8_t smem_raw[];
  const uint32_t sb = (smem_u32(smem_raw) + 1023) & ~1023u;
  uint8_t* smem = smem_raw + (sb - smem_u32(smem_raw));
  const int warp = uniform_warp_id(), lane = threadIdx.x & 31;
  const uint32_t rank = cluster_rank();
  const int pair = blockIdx.x >> 1;

  if (threadIdx.x == 0) {
    for (int s = 0; s < G_STAGES0; s++) { mbar_init(sb + B_GFULL + 8 * s, 1); mbar_init(sb + B_GEMPTY + 8 * s, 2); }
    mbar_init(sb + B_T0DONE, 2); mbar_init(sb + B_LFREE, 2); mbar_init(sb + B_ADONE, 4);
    for (int s = 0; s < KV_STAGES; s++) { mbar_init(sb + B_KFULL + 8 * s, 1); mbar_init(sb + B_KEMPTY + 8 * s, KV_MC ? 4 : 2); }
    mbar_init(sb + B_SFULL, 128); mbar_init(sb + B_SFREE, 1);
    for (int w = 0; w < 2; w++) { mbar_init(sb + B_OFULL + 8 * w, 128); mbar_init(sb + B_OFREE + 8 * w, 1); }
    mbar_init(sb + B_RDY, 1); mbar_init(sb + B_VERD, 1);
    fence_mbar_init();
  }
  if (threadIdx.x == 32) *reinterpret_cast<volatile uint32_t*>(smem + S_EPOCH) = *reinterpret_cast<volatile uint32_t*>(&g_epoch);
  if (threadIdx.x < 256) reinterpret_cast<uint32_t*>(smem + S_ONES)[threadIdx.x] = 0x3F803F80u;
  fence_proxy_async_smem();
  __syncthreads();
  cluster_sync_relaxed();

  if (warp < 4) {
    reg_dealloc<M_PREGS>();
    const uint32_t epoch = *reinterpret_cast<volatile uint32_t*>(smem + S_EPOCH);
    if (warp == 0) {
      if (lane == 0) {
        GPipe r{0, 0xffffffffu};
        for (int i = 0; i < MAXT; i++) {
          const Tile t = decode_tile(prm.gt[pair][i]);
          if (t.type == T_NONE) break;
          const int rb = t.mp * 2 + (int)rank;
          const CUtensorMap* mw; int c0, c2;
          if (t.type == T_AKV || t.type == T_BKV) { mw = &prm.wkv[t.type == T_BKV]; c0 = 64 * t.idx; c2 = 1; }
          else { mw = &prm.wblk[t.type == T_AQ ? 0 : t.type == T_BQ ? 1 : t.type == T_BOUT ? 2 : 3]; c0 = 0; c2 = 2 * t.idx; }
          const bool isout = t.type >= T_BOUT;
          const CUtensorMap* ma = &prm.x[t.type <= T_AQ ? 0 : 1];
          const uint8_t* img = g_o + (size_t)((t.type == T_BOUT ? 16 : 0) + rb) * NH * 8192;
          if (t.type == T_BOUT) cnt_wait(C_BQ + t.mp, epoch, 16);
          const int kt0 = 0, kt1 = 16;
          const bool late = t.type == T_AOUT && t.mp >= 4;
          for (int kt = kt0; kt < kt1; kt++) {
            if (t.type >= T_AOUT && (kt & 7) == 0) cnt_wait(C_ATT + t.mp * 2 + (kt >> 3), epoch, 64);
            const bool wide = i == 0 || (late && kt >= 8);
            if (late && kt == 8) {
              HWAIT(sb + B_ADONE, 0);
              HWAIT(sb + B_LFREE, 0);
            }
#if M_HOLD >= 0
            if (i == 1 && kt == M_HOLD && prm.na[pair] > 0) HWAIT(sb + B_VERD, 0);
#endif
            mbar_wait(sb + B_GEMPTY + 8 * r.slot, r.parity());
            const uint32_t full = sb + B_GFULL + 8 * r.slot, sa = sb + g_slot_off(r.slot);
            mbar_expect_tx(full, 32768);
            tma_load_3d_mc(sa + 16384 + rank * 8192, mw, full, c0, kt * 64 + (int)rank * 32, c2, (uint16_t)3);
            if (isout) bulk_load_1d(sa, img + kt * 16384, 16384, full);
            else tma_load_2d(sa, ma, full, kt * 64, rb * 128);
            r.advance(wide ? G_STAGES0 : G_STAGES);
          }
          if (i == 0) r.slot = 0;
          if (t.type == T_BQ) {
            cnt_wait2(C_KVB + 2 * t.idx, 1, C_KVB + 2 * t.idx + 1, 1, epoch);
            HWAIT(sb + B_GEMPTY + 8 * r.slot, r.parity());
            const uint32_t full = sb + B_GFULL + 8 * r.slot;
            mbar_expect_tx(full, 4 * 2560);
            bulk_load_1d(sb + r.slot * G_STAGE, g_kvb + t.idx * 4 * 640, 4 * 2560, full);
            r.advance(G_STAGES);
          }
        }
      }
    } else if (warp == 1) {
      const int na = prm.na[pair];
      KvRing r{0, 1};
      if (lane == 0 && na > 0) HWAIT(sb + B_T0DONE, 0);
      for (int it = 0; it < na; it++) {
        const int h = prm.at[pair][it] & 31, mp = prm.at[pair][it] >> 5;
        const uint8_t* src = g_qkv + (size_t)((1 + rank) * NH + h) * SEQ * 64;
        auto load_stage = [&](int j) {
          HWAIT(sb + B_KEMPTY + 8 * r.slot, r.phase);
          const uint32_t full = sb + B_KFULL + 8 * r.slot;
          mbar_expect_tx(full, 16384);
          if (KV_MC) {
            bulk_load_1d_mc(sb + S_KV + r.slot * 16384 + rank * 8192, src + j * 8192, 8192, full, (uint16_t)3);
          } else {
            const uint8_t* ks = g_qkv + (size_t)(NH + h) * SEQ * 64 + j * 8192;
            bulk_load_1d(sb + S_KV + r.slot * 16384, ks, 8192, full);
            bulk_load_1d(sb + S_KV + r.slot * 16384 + 8192, ks + (size_t)NH * SEQ * 64, 8192, full);
          }
          r.advance();
        };
        if (lane == 0) {
          cnt_wait2(C_AKV + (h >> 1), 16, C_AQ + (h >> 2) * 8 + mp, 2, epoch);
          TIMR(3, 4 * it);
          mbar_arrive(sb + B_RDY);
          load_stage(0);
          TIMR(3, 4 * it + 1);
        }
        __syncwarp();
        {
          const uint4 kq = __ldcg(reinterpret_cast<const uint4*>(g_stats + (NH + h) * 128) + lane);
          const uint4 vq = __ldcg(reinterpret_cast<const uint4*>(g_stats + (2 * NH + h) * 128) + lane);
          const uint4 qq = __ldcg(reinterpret_cast<const uint4*>(g_stats + h * 128 + mp * 16 + rank * 8) + (lane & 1));
          const float km = __uint_as_float(__reduce_max_sync(0xffffffffu, max(max(kq.x, kq.y), max(kq.z, kq.w))));
          const float vm = __uint_as_float(__reduce_max_sync(0xffffffffu, max(max(vq.x, vq.y), max(vq.z, vq.w))));
          const float qm = __uint_as_float(max(max(qq.x, qq.y), max(qq.z, qq.w)));
          const bool ok = (qm * km <= 4000.f) && (vm <= 1.0e21f) && (vm >= 3.0e-17f);
          if (lane < 2) reinterpret_cast<volatile uint32_t*>(smem + S_FAST)[it * 2 + lane] = ok ? 1u : 0u;
          __syncwarp();
          if (lane == 0) { mbar_arrive(sb + B_VERD); TIMR(3, 4 * it + 2); }
        }
        if (lane == 0) { for (int j = 1; j < 16; j++) load_stage(j); }
        __syncwarp();
      }
    } else if (warp == 2) {
      const uint32_t stg = sb + S_STG;
      for (int i = 0; i < MAXT; i++) {
        const Tile t = decode_tile(prm.gt[pair][i]);
        if (t.type == T_NONE) break;
        const int rb = t.mp * 2 + (int)rank;
        uint32_t last = 0;
        if (lane == 0) {
          HWAIT(sb + B_SFULL, i & 1);
          if (i < 8) TIMR(2, 4 * i);
          if (t.type <= T_AQ) {
            for (int s = 0; s < 4; s++) {
              const int ph = t.type == T_AQ ? 4 * t.idx + s : (1 + (s >> 1)) * NH + 2 * t.idx + (s & 1);
              bulk_store_1d(g_qkv + ((size_t)ph * SEQ + rb * 128) * 64, stg + s * 8192, 8192);
              bulk_store_1d(g_stats + ph * 128 + rb * 8, sb + S_STAT + s * 32, 32);
            }
          } else if (t.type == T_BKV) {
            for (int s = 0; s < 2; s++) bulk_reduce_add_f32(g_kv + (2 * t.idx + s) * 1280, stg + s * 8192, 5120);
          } else if (t.type == T_BQ) {
            bulk_store_1d(g_o + (size_t)((16 + rb) * NH + 4 * t.idx) * 8192, stg, 4 * 8192);
          } else {
            if (t.type == T_AOUT2) {
              bulk_wait<0>();
              for (int s = 0; s < 2; s++) tma_reduce_add_2d(&prm.out, stg + s * 16384, t.idx * 128 + s * 64, rb * 128);
            } else {
              for (int s = 0; s < 2; s++) tma_store_2d(&prm.out, stg + s * 16384, (t.type == T_BOUT ? DM : 0) + t.idx * 128 + s * 64, rb * 128);
            }
          }
          bulk_commit();
          bulk_wait_read<0>();
          if (i < 8) TIMR(2, 4 * i + 1);
          mbar_arrive(sb + B_SFREE);
          if (i + 1 < MAXT && (prm.gt[pair][i + 1] & 7) == T_AOUT && (prm.gt[pair][i + 1] >> 7) >= 4) {
            mbar_arrive_cluster(sb + B_LFREE, 0); mbar_arrive_cluster(sb + B_LFREE, 1); }
          if (t.type < T_BOUT) {
            bulk_wait<0>();
            TIMR(2, 4 * i + 2);
            const int c = t.type == T_AKV ? C_AKV + t.idx : t.type == T_AQ ? C_AQ + t.idx * 8 + t.mp : t.type == T_BKV ? C_BKV + t.idx : C_BQ + t.mp;
            if (t.type == T_BKV) last = cnt_add(c) + 1 == epoch * 16 + 16 ? 1u : 0u;
            else cnt_red(c, 1);
            TIMR(2, 4 * i + 3);
          }
        }
        last = __shfl_sync(0xffffffffu, last, 0);
        if (last) {
          asm volatile("fence.acq_rel.gpu;" ::: "memory");
          fence_proxy_async_all();
#pragma unroll 2
          for (int c = lane; c < 320; c += 32) {
            const int hh = c / 160, rr = c % 160, d = rr / 5, g = rr % 5;
            float4* src = reinterpret_cast<float4*>(g_kv + (2 * t.idx + hh) * 1280 + d * 40 + g * 8);
            const float4 a = __ldcg(src), b = __ldcg(src + 1);
            uint4 v;
            v.x = pack_bf16(a.x, a.y); v.y = pack_bf16(a.z, a.w); v.z = pack_bf16(b.x, b.y); v.w = pack_bf16(b.z, b.w);
            *reinterpret_cast<uint4*>(g_kvb + (2 * t.idx + hh) * 640 + (d >> 3) * 160 + g * 32 + (d & 7) * 4) = v;
            __stcg(src, make_float4(0.f, 0.f, 0.f, 0.f)); __stcg(src + 1, make_float4(0.f, 0.f, 0.f, 0.f));
          }
          __threadfence();
          fence_proxy_async_all();
          __syncwarp();
          if (lane == 0) cnt_red(C_KVB + t.idx, 1);
        }
        __syncwarp();
      }
      if (lane == 0) bulk_wait_read<0>();
    } else {
      if (lane == 0) {
        if (atomicAdd(&g_exit, 1u) == gridDim.x - 1) { g_exit = 0; __threadfence(); atomicAdd(&g_epoch, 1u); }
        const int na = prm.na[pair];
        for (int it = 0; it < na; it++) {
          const int h = prm.at[pair][it] & 31, mp = prm.at[pair][it] >> 5;
          uint8_t* dst = g_o + (size_t)((mp * 2 + rank) * NH + h) * 8192;
          for (int w = 0; w < 2; w++) {
            HWAIT(sb + B_OFULL + 8 * w, it & 1);
            bulk_store_1d(dst + w * 4096, sb + S_OST + w * 4096, 4096);
            bulk_commit();
          }
          bulk_wait_read<0>();
          mbar_arrive(sb + B_OFREE); mbar_arrive(sb + B_OFREE + 8);
          bulk_wait<0>();
          cnt_red(C_ATT + mp * 2 + (h >> 4), 2);
        }
      }
    }
    __syncwarp();
    cluster_sync_relaxed();
  } else if (warp < 12) {
    if constexpr (M_AREGS > 128) reg_alloc<M_AREGS>(); else reg_dealloc<M_AREGS>();
    const int wg = (warp >> 2) - 1, wq = warp & 3, tid = threadIdx.x & 127;
    const int qd = lane & 3, r8 = lane >> 2;
    const int na = prm.na[pair];
    auto release = [&](int slot) {
      if (KV_MC) mbar_arrive_pair(sb + B_KEMPTY + 8 * slot, tid);
      else { if (tid == 0) mbar_arrive(sb + B_KEMPTY + 8 * slot); __syncwarp(); }
    };
    auto load_q = [&](uint32_t (&q)[8], int it) {
      const int h = prm.at[pair][it] & 31, mp = prm.at[pair][it] >> 5;
      const int row = mp * 256 + (int)rank * 128 + wg * 64 + wq * 16 + r8;
      const uint8_t* qp = g_qkv + ((size_t)h * SEQ + row) * 64 + qd * 4;
      const int sw = (row >> 1) & 3;
#pragma unroll
      for (int ks = 0; ks < 2; ks++) {
        q[4 * ks + 0] = __ldcg(reinterpret_cast<const uint32_t*>(qp + (((2 * ks) ^ sw) << 4)));
        q[4 * ks + 1] = __ldcg(reinterpret_cast<const uint32_t*>(qp + (((2 * ks) ^ sw) << 4) + 512));
        q[4 * ks + 2] = __ldcg(reinterpret_cast<const uint32_t*>(qp + (((2 * ks + 1) ^ sw) << 4)));
        q[4 * ks + 3] = __ldcg(reinterpret_cast<const uint32_t*>(qp + (((2 * ks + 1) ^ sw) << 4) + 512));
      }
    };
    uint32_t q[8], qn[8];
    KvRing r{0, 0};
    if (na > 0) {
      mbar_wait(sb + B_RDY, 0);
      load_q(q, 0);
    }
    for (int it = 0; it < na; it++) {
      TIMW(tid == 0 && wg == 0, 1, 2 * it);
      mbar_wait(sb + B_VERD, it & 1);
      mbar_wait(sb + B_KFULL + 8 * r.slot, r.phase);
      const bool fast = __all_sync(0xffffffffu, reinterpret_cast<volatile uint32_t*>(smem + S_FAST)[it * 2 + wg] != 0);
      float o[20];
#pragma unroll
      for (int i = 0; i < 20; i++) o[i] = 0.f;
      fence_regs(o);
      auto tail_hook = [&]() {
        if (it + 1 < na) {
          mbar_wait(sb + B_RDY, (it + 1) & 1);
          load_q(qn, it + 1);
        }
      };
      if (fast) attn_item_fast(o, q, sb, r, release, tail_hook);
      else attn_item_safe(o, q, sb, r, release, tail_hook);
      const float i0 = rcp_approx(o[16]), i1 = rcp_approx(o[18]);
      uint32_t p[8];
#pragma unroll
      for (int j = 0; j < 4; j++) {
        p[2 * j] = pack_bf16(o[4 * j] * i0, o[4 * j + 1] * i0);
        p[2 * j + 1] = pack_bf16(o[4 * j + 2] * i1, o[4 * j + 3] * i1);
      }
      if (it > 0) mbar_wait(sb + B_OFREE + 8 * wg, (it - 1) & 1);
      stage_slot(sb + S_OST + wg * 4096, 0, 0, wq, lane, p);
      fence_proxy_async_smem();
      mbar_arrive(sb + B_OFULL + 8 * wg);
#pragma unroll
      for (int i = 0; i < 8; i++) q[i] = qn[i];
      TIMW(tid == 0 && wg == 0, 1, 2 * it + 1);
    }
    mbar_arrive_pair(sb + B_ADONE, tid);
    __syncwarp();
    cluster_sync_relaxed();
  } else {
    reg_alloc<M_GREGS>();
    GPipe r{0, 0u};
    for (int i = 0; i < MAXT; i++) {
      const Tile t = decode_tile(__shfl_sync(0xffffffffu, (uint32_t)prm.gt[pair][i], 0));
      if (t.type == T_NONE) break;
      TIMW((threadIdx.x & 127) == 0, 0, 3 * i);
      tile_n128(t, i, sb, smem, r, warp, lane, rank);
      fence_proxy_async_smem();
      mbar_arrive(sb + B_SFULL);
      TIMW((threadIdx.x & 127) == 0, 0, 3 * i + 2);
    }
    __syncwarp();
    cluster_sync_relaxed();
  }
}
#include <string.h>

typedef CUresult (*PFN_encodeTiled)(CUtensorMap*, CUtensorMapDataType, cuuint32_t, void*, const cuuint64_t*, const cuuint64_t*,
                                    const cuuint32_t*, const cuuint32_t*, CUtensorMapInterleave, CUtensorMapSwizzle,
                                    CUtensorMapL2promotion, CUtensorMapFloatOOBfill);

static PFN_encodeTiled get_encode() {
  static PFN_encodeTiled fn = nullptr;
  if (!fn) {
    void* p = nullptr;
    cudaDriverEntryPointQueryResult q;
    cudaGetDriverEntryPoint("cuTensorMapEncodeTiled", &p, cudaEnableDefault, &q);
    fn = (PFN_encodeTiled)p;
  }
  return fn;
}
static void make_map(CUtensorMap* m, const void* base, int rank, const cuuint64_t* dims, const cuuint64_t* strides, const cuuint32_t* box) {
  cuuint32_t es[3] = {1, 1, 1};
  get_encode()(m, CU_TENSOR_MAP_DATA_TYPE_BFLOAT16, rank, const_cast<void*>(base), dims, strides, box, es, CU_TENSOR_MAP_INTERLEAVE_NONE,
               CU_TENSOR_MAP_SWIZZLE_128B, CU_TENSOR_MAP_L2_PROMOTION_L2_256B, CU_TENSOR_MAP_FLOAT_OOB_FILL_NONE);
}
static void map_2d(CUtensorMap* m, const void* base, int rows, int cols) {
  cuuint64_t dims[2] = {(cuuint64_t)cols, (cuuint64_t)rows};
  cuuint64_t strides[1] = {(cuuint64_t)cols * 2};
  cuuint32_t box[2] = {64, 128};
  make_map(m, base, 2, dims, strides, box);
}
static void map_parts(CUtensorMap* m, const void* base, int np) {
  cuuint64_t dims[3] = {1024, 1024, 3};
  cuuint64_t strides[2] = {3072 * 2, 1024 * 2};
  cuuint32_t box[3] = {64, 32, (cuuint32_t)np};
  make_map(m, base, 3, dims, strides, box);
}
static void map_blk(CUtensorMap* m, const void* base, int N) {
  cuuint64_t dims[3] = {64, 1024, (cuuint64_t)(N / 64)};
  cuuint64_t strides[2] = {(cuuint64_t)N * 2, 128};
  cuuint32_t box[3] = {64, 32, 2};
  make_map(m, base, 3, dims, strides, box);
}

#define SCHED_T3 100000.0
#define SCHED_T4 125000.0
#define SCHED_SLOW 1.8
static void build_schedule(MegaParams& P) {
  auto enc = [](int type, int idx, int mp) { return (uint16_t)(type | (idx << 3) | (mp << 7)); };
  for (int p = 0; p < NPAIR; p++) {
    for (int i = 0; i < MAXT; i++) P.gt[p][i] = T_NONE;
    P.na[p] = 0;
    if (p >= 64) continue;
    const int hi = p >> 3, lo = p & 7;
    int n = 0;
    P.gt[p][n++] = hi < 4 ? enc(T_AKV, hi, lo) : hi < 6 ? enc(T_AQ, hi - 4, lo) : enc(T_AKV, hi - 2, lo);
    P.gt[p][n++] = hi < 2 ? enc(T_AKV, 6 + hi, lo) : hi < 4 ? enc(T_AQ, hi, lo) : enc(T_AKV, 4 + hi, lo);
    P.gt[p][n++] = hi < 4 ? enc(T_AKV, 12 + hi, lo) : enc(T_AQ, hi, lo);
    P.gt[p][n++] = enc(T_BKV, hi, lo);
    P.gt[p][n++] = enc(T_BKV, 8 + hi, lo);
    P.gt[p][n++] = enc(T_BQ, hi, lo);
    if (p < 32) {
      P.gt[p][n++] = enc(T_AOUT, lo, hi);
      P.gt[p][n++] = enc(T_BOUT, lo, 4 + hi);
    } else {
      P.gt[p][n++] = enc(T_BOUT, lo, hi - 4);
      P.gt[p][n++] = enc(T_AOUT, lo, hi);
    }
    for (int r = 0; r < 4; r++) {
      int h, mp;
      if (r < 2) { h = r * 8 + hi; mp = lo; }
      else { h = 16 + (p & 15); mp = (r - 2) * 4 + (p >> 4); }
      P.at[p][P.na[p]++] = (uint8_t)(h | (mp << 5));
    }
  }
}

static void build_params(MegaParams& P, void* const* d_in, void* d_out) {
  map_2d(&P.x[0], d_in[0], SEQ, DM);
  map_2d(&P.x[1], d_in[3], SEQ, DM);
  map_parts(&P.wkv[0], d_in[1], 2);
  map_parts(&P.wkv[1], d_in[4], 2);
  map_blk(&P.wblk[0], d_in[1], 3 * DM);
  map_blk(&P.wblk[1], d_in[4], 3 * DM);
  map_blk(&P.wblk[2], d_in[5], DM);
  map_blk(&P.wblk[3], d_in[2], DM);
  map_2d(&P.out, d_out, SEQ, 2 * DM);
  P.xa = (const uint8_t*)d_in[0]; P.wa = (const uint8_t*)d_in[1];
  build_schedule(P);
}

extern "C" void kernel_launch(void* const* d_in, const int* in_sizes, int n_in, void* d_out, int out_size) {
  static bool attr_done = false;
  if (!attr_done) {
    attr_done = true;
    cudaFuncSetAttribute(mega_kernel, cudaFuncAttributeMaxDynamicSharedMemorySize, MEGA_SMEM);
  }
  MegaParams P;
  memset(&P, 0, sizeof(P));
  build_params(P, d_in, d_out);
  mega_kernel<<<2 * NPAIR, 512, MEGA_SMEM, cudaStreamPerThread>>>(P);
}
```

```cpp
#include <cuda_runtime.h>
#include <cuda_bf16.h>
#include <cuda.h>
#include <stdint.h>
#include <string.h>
#include <type_traits>

__device__ __forceinline__ uint32_t smem_u32(const void* p) { return (uint32_t)__cvta_generic_to_shared(p); }

__device__ __forceinline__ void mbar_init(uint32_t bar, uint32_t count) {
  asm volatile("mbarrier.init.shared::cta.b64 [%0], %1;" ::"r"(bar), "r"(count) : "memory");
}
__device__ __forceinline__ void mbar_expect_tx(uint32_t bar, uint32_t bytes) {
  asm volatile("mbarrier.arrive.expect_tx.shared::cta.b64 _, [%0], %1;" ::"r"(bar), "r"(bytes) : "memory");
}
__device__ __forceinline__ void mbar_arrive(uint32_t bar) {
  asm volatile("mbarrier.arrive.shared::cta.b64 _, [%0];" ::"r"(bar) : "memory");
}
__device__ __forceinline__ void mbar_arrive_cluster(uint32_t bar, uint32_t rank) {
  asm volatile(
      "{\n.reg .b32 ra;\n"
      "mapa.shared::cluster.u32 ra, %0, %1;\n"
      "mbarrier.arrive.shared::cluster.b64 _, [ra];\n}"
      ::"r"(bar), "r"(rank) : "memory");
}
__device__ __forceinline__ void mbar_arrive_pair(uint32_t bar, int tid) {
  if (tid < 2) mbar_arrive_cluster(bar, tid);
  __syncwarp();
}
__device__ __forceinline__ void mbar_wait(uint32_t bar, uint32_t parity) {
  asm volatile(
      "{\n.reg .pred p;\n.reg .u32 c;\n"
      "mbarrier.try_wait.parity.shared::cta.b64 p, [%0], %1;\n"
      "@p bra WAIT_DONE;\n"
      "mov.u32 c, 0;\n"
      "WAIT_LOOP:\n"
      "mbarrier.try_wait.parity.shared::cta.b64 p, [%0], %1;\n"
      "@p bra WAIT_DONE;\n"
      "add.u32 c, c, 1;\n"
      "setp.lt.u32 p, c, 16777216;\n"
      "@p bra WAIT_LOOP;\n"
      "trap;\n"
      "WAIT_DONE:\n}"
      ::"r"(bar), "r"(parity) : "memory");
}
__device__ __forceinline__ void mbar_wait_long(uint32_t bar, uint32_t parity) {
  asm volatile(
      "{\n.reg .pred p;\n.reg .u32 c;\n"
      "mbarrier.try_wait.parity.shared::cta.b64 p, [%0], %1;\n"
      "@p bra WAIT_DONE;\n"
      "mov.u32 c, 0;\n"
      "WAIT_LOOP:\n"
      "mbarrier.try_wait.parity.shared::cta.b64 p, [%0], %1, 20000;\n"
      "@p bra WAIT_DONE;\n"
      "add.u32 c, c, 1;\n"
      "setp.lt.u32 p, c, 500000;\n"
      "@p bra WAIT_LOOP;\n"
      "trap;\n"
      "WAIT_DONE:\n}"
      ::"r"(bar), "r"(parity) : "memory");
}
__device__ __forceinline__ void fence_mbar_init() { asm volatile("fence.mbarrier_init.release.cluster;" ::: "memory"); }
__device__ __forceinline__ void fence_proxy_async_smem() { asm volatile("fence.proxy.async.shared::cta;" ::: "memory"); }
__device__ __forceinline__ void fence_proxy_async_all() { asm volatile("fence.proxy.async;" ::: "memory"); }
__device__ __forceinline__ void cluster_sync() {
  asm volatile("barrier.cluster.arrive.relaxed.aligned;\nbarrier.cluster.wait.aligned;" ::: "memory");
}
__device__ __forceinline__ uint32_t cluster_rank() {
  uint32_t r;
  asm("mov.u32 %0, %%cluster_ctarank;" : "=r"(r));
  return r;
}
__device__ __forceinline__ void named_bar_sync(int id, int nthreads) {
  asm volatile("bar.sync %0, %1;" ::"r"(id), "r"(nthreads) : "memory");
}
template <int R> __device__ __forceinline__ void reg_alloc() { asm volatile("setmaxnreg.inc.sync.aligned.u32 %0;" ::"n"(R)); }
template <int R> __device__ __forceinline__ void reg_dealloc() { asm volatile("setmaxnreg.dec.sync.aligned.u32 %0;" ::"n"(R)); }

__device__ __forceinline__ void prefetch_tmap(const CUtensorMap* m) {
  asm volatile("prefetch.tensormap [%0];" ::"l"(m) : "memory");
}
__device__ __forceinline__ void tma_load_2d(uint32_t dst, const CUtensorMap* m, uint32_t bar, int c0, int c1) {
  asm volatile("cp.async.bulk.tensor.2d.shared::cluster.global.mbarrier::complete_tx::bytes [%0], [%1, {%3, %4}], [%2];"
               ::"r"(dst), "l"(m), "r"(bar), "r"(c0), "r"(c1) : "memory");
}
__device__ __forceinline__ void tma_load_3d_mc(uint32_t dst, const CUtensorMap* m, uint32_t bar, int c0, int c1, int c2, uint16_t mask) {
  asm volatile("cp.async.bulk.tensor.3d.shared::cluster.global.mbarrier::complete_tx::bytes.multicast::cluster [%0], [%1, {%3, %4, %5}], [%2], %6;"
               ::"r"(dst), "l"(m), "r"(bar), "r"(c0), "r"(c1), "r"(c2), "h"(mask) : "memory");
}
__device__ __forceinline__ void tma_store_2d(const CUtensorMap* m, uint32_t src, int c0, int c1) {
  asm volatile("cp.async.bulk.tensor.2d.global.shared::cta.bulk_group [%0, {%2, %3}], [%1];"
               ::"l"(m), "r"(src), "r"(c0), "r"(c1) : "memory");
}
__device__ __forceinline__ void bulk_load_1d(uint32_t dst, const void* src, uint32_t bytes, uint32_t bar) {
  asm volatile("cp.async.bulk.shared::cluster.global.mbarrier::complete_tx::bytes [%0], [%1], %2, [%3];"
               ::"r"(dst), "l"(src), "r"(bytes), "r"(bar) : "memory");
}
__device__ __forceinline__ void bulk_load_1d_mc(uint32_t dst, const void* src, uint32_t bytes, uint32_t bar, uint16_t mask) {
  asm volatile("cp.async.bulk.shared::cluster.global.mbarrier::complete_tx::bytes.multicast::cluster [%0], [%1], %2, [%3], %4;"
               ::"r"(dst), "l"(src), "r"(bytes), "r"(bar), "h"(mask) : "memory");
}
__device__ __forceinline__ void bulk_store_1d(void* dst, uint32_t src, uint32_t bytes) {
  asm volatile("cp.async.bulk.global.shared::cta.bulk_group [%0], [%1], %2;" ::"l"(dst), "r"(src), "r"(bytes) : "memory");
}
__device__ __forceinline__ void bulk_reduce_add_f32(void* dst, uint32_t src, uint32_t bytes) {
  asm volatile("cp.reduce.async.bulk.global.shared::cta.bulk_group.add.f32 [%0], [%1], %2;" ::"l"(dst), "r"(src), "r"(bytes) : "memory");
}
__device__ __forceinline__ void bulk_commit() { asm volatile("cp.async.bulk.commit_group;" ::: "memory"); }
template <int N> __device__ __forceinline__ void bulk_wait_read() { asm volatile("cp.async.bulk.wait_group.read %0;" ::"n"(N) : "memory"); }
template <int N> __device__ __forceinline__ void bulk_wait() { asm volatile("cp.async.bulk.wait_group %0;" ::"n"(N) : "memory"); }

__device__ __forceinline__ void wg_fence() { asm volatile("wgmma.fence.sync.aligned;" ::: "memory"); }
__device__ __forceinline__ void wg_commit() { asm volatile("wgmma.commit_group.sync.aligned;" ::: "memory"); }
template <int N> __device__ __forceinline__ void wg_wait() { asm volatile("wgmma.wait_group.sync.aligned %0;" ::"n"(N) : "memory"); }

__device__ __forceinline__ uint32_t desc_lo(uint32_t addr, uint32_t lbo) { return ((addr & 0x3FFFF) >> 4) | (((lbo >> 4) & 0x3FFF) << 16); }
constexpr uint32_t HI_SW64_512 = (512 >> 4) | (2u << 30);
constexpr uint32_t HI_SW128_1024 = (1024 >> 4) | (1u << 30);
constexpr uint32_t HI_NOSW_128 = (128 >> 4);

__device__ __forceinline__ int uniform_warp_id() { return __shfl_sync(0xffffffffu, (int)(threadIdx.x >> 5), 0); }
__device__ __forceinline__ void stmatrix_x4(uint32_t addr, uint32_t r0, uint32_t r1, uint32_t r2, uint32_t r3) {
  asm volatile("stmatrix.sync.aligned.m8n8.x4.shared.b16 [%0], {%1, %2, %3, %4};" ::"r"(addr), "r"(r0), "r"(r1), "r"(r2), "r"(r3) : "memory");
}
__device__ __forceinline__ uint32_t pack_bf16(float lo, float hi) {
  uint32_t r;
  asm("cvt.rn.bf16x2.f32 %0, %1, %2;" : "=r"(r) : "f"(hi), "f"(lo));
  return r;
}
__device__ __forceinline__ float ex2_approx(float x) {
  float y;
  asm("ex2.approx.ftz.f32 %0, %1;" : "=f"(y) : "f"(x));
  return y;
}
__device__ __forceinline__ float ex2_ordered(float x) {
  float y;
  asm volatile("ex2.approx.ftz.f32 %0, %1;" : "=f"(y) : "f"(x));
  return y;
}
__device__ __forceinline__ float rcp_approx(float x) {
  float y;
  asm("rcp.approx.ftz.f32 %0, %1;" : "=f"(y) : "f"(x));
  return y;
}
template <int NR> __device__ __forceinline__ void fence_regs(float (&d)[NR]) {
#pragma unroll
  for (int i = 0; i < NR; i++) asm volatile("" : "+f"(d[i])::"memory");
}
template <int I> using IC = std::integral_constant<int, I>;
template <int N, class F, int I = 0> __device__ __forceinline__ void static_for(F&& f) {
  if constexpr (I < N) { f(IC<I>{}); static_for<N, F, I + 1>(static_cast<F&&>(f)); }
}

template <uint32_t HA, uint32_t HB>
__device__ __forceinline__ void wgmma_ss_n128_tb(float (&d)[64], uint32_t la, uint32_t lb) {
  asm volatile("{\n.reg .pred p;\n.reg .b64 da, db;\n"
    "mov.b64 da, {%64, %66};\nmov.b64 db, {%65, %67};\n"
    "setp.ne.b32 p, 1, 0;\n"
    "wgmma.mma_async.sync.aligned.m64n128k16.f32.bf16.bf16 "
    "{%0, %1, %2, %3, %4, %5, %6, %7, %8, %9, %10, %11, %12, %13, %14, %15, "
    "%16, %17, %18, %19, %20, %21, %22, %23, %24, %25, %26, %27, %28, %29, %30, %31, "
    "%32, %33, %34, %35, %36, %37, %38, %39, %40, %41, %42, %43, %44, %45, %46, %47, "
    "%48, %49, %50, %51, %52, %53, %54, %55, %56, %57, %58, %59, %60, %61, %62, %63}, "
    "da, db, p, 1, 1, 0, 1;\n}\n"
    : "+f"(d[0]), "+f"(d[1]), "+f"(d[2]), "+f"(d[3]), "+f"(d[4]), "+f"(d[5]), "+f"(d[6]), "+f"(d[7]),
      "+f"(d[8]), "+f"(d[9]), "+f"(d[10]), "+f"(d[11]), "+f"(d[12]), "+f"(d[13]), "+f"(d[14]), "+f"(d[15]),
      "+f"(d[16]), "+f"(d[17]), "+f"(d[18]), "+f"(d[19]), "+f"(d[20]), "+f"(d[21]), "+f"(d[22]), "+f"(d[23]),
      "+f"(d[24]), "+f"(d[25]), "+f"(d[26]), "+f"(d[27]), "+f"(d[28]), "+f"(d[29]), "+f"(d[30]), "+f"(d[31]),
      "+f"(d[32]), "+f"(d[33]), "+f"(d[34]), "+f"(d[35]), "+f"(d[36]), "+f"(d[37]), "+f"(d[38]), "+f"(d[39]),
      "+f"(d[40]), "+f"(d[41]), "+f"(d[42]), "+f"(d[43]), "+f"(d[44]), "+f"(d[45]), "+f"(d[46]), "+f"(d[47]),
      "+f"(d[48]), "+f"(d[49]), "+f"(d[50]), "+f"(d[51]), "+f"(d[52]), "+f"(d[53]), "+f"(d[54]), "+f"(d[55]),
      "+f"(d[56]), "+f"(d[57]), "+f"(d[58]), "+f"(d[59]), "+f"(d[60]), "+f"(d[61]), "+f"(d[62]), "+f"(d[63])
    : "r"(la), "r"(lb), "n"(HA), "n"(HB));
}
template <uint32_t HA, uint32_t HB>
__device__ __forceinline__ void wgmma_ss_n128_tb_z(float (&d)[64], uint32_t la, uint32_t lb) {
  asm volatile("{\n.reg .pred p;\n.reg .b64 da, db;\n"
    "mov.b64 da, {%64, %66};\nmov.b64 db, {%65, %67};\n"
    "setp.ne.b32 p, 0, 0;\n"
    "wgmma.mma_async.sync.aligned.m64n128k16.f32.bf16.bf16 "
    "{%0, %1, %2, %3, %4, %5, %6, %7, %8, %9, %10, %11, %12, %13, %14, %15, "
    "%16, %17, %18, %19, %20, %21, %22, %23, %24, %25, %26, %27, %28, %29, %30, %31, "
    "%32, %33, %34, %35, %36, %37, %38, %39, %40, %41, %42, %43, %44, %45, %46, %47, "
    "%48, %49, %50, %51, %52, %53, %54, %55, %56, %57, %58, %59, %60, %61, %62, %63}, "
    "da, db, p, 1, 1, 0, 1;\n}\n"
    : "=f"(d[0]), "=f"(d[1]), "=f"(d[2]), "=f"(d[3]), "=f"(d[4]), "=f"(d[5]), "=f"(d[6]), "=f"(d[7]),
      "=f"(d[8]), "=f"(d[9]), "=f"(d[10]), "=f"(d[11]), "=f"(d[12]), "=f"(d[13]), "=f"(d[14]), "=f"(d[15]),
      "=f"(d[16]), "=f"(d[17]), "=f"(d[18]), "=f"(d[19]), "=f"(d[20]), "=f"(d[21]), "=f"(d[22]), "=f"(d[23]),
      "=f"(d[24]), "=f"(d[25]), "=f"(d[26]), "=f"(d[27]), "=f"(d[28]), "=f"(d[29]), "=f"(d[30]), "=f"(d[31]),
      "=f"(d[32]), "=f"(d[33]), "=f"(d[34]), "=f"(d[35]), "=f"(d[36]), "=f"(d[37]), "=f"(d[38]), "=f"(d[39]),
      "=f"(d[40]), "=f"(d[41]), "=f"(d[42]), "=f"(d[43]), "=f"(d[44]), "=f"(d[45]), "=f"(d[46]), "=f"(d[47]),
      "=f"(d[48]), "=f"(d[49]), "=f"(d[50]), "=f"(d[51]), "=f"(d[52]), "=f"(d[53]), "=f"(d[54]), "=f"(d[55]),
      "=f"(d[56]), "=f"(d[57]), "=f"(d[58]), "=f"(d[59]), "=f"(d[60]), "=f"(d[61]), "=f"(d[62]), "=f"(d[63])
    : "r"(la), "r"(lb), "n"(HA), "n"(HB));
}
template <uint32_t HA, uint32_t HB>
__device__ __forceinline__ void wgmma_ss_n40_tb_ta(float (&d)[20], uint32_t la, uint32_t lb) {
  asm volatile("{\n.reg .pred p;\n.reg .b64 da, db;\n"
    "mov.b64 da, {%20, %22};\nmov.b64 db, {%21, %23};\n"
    "setp.ne.b32 p, 1, 0;\n"
    "wgmma.mma_async.sync.aligned.m64n40k16.f32.bf16.bf16 "
    "{%0, %1, %2, %3, %4, %5, %6, %7, %8, %9, %10, %11, %12, %13, %14, %15, "
    "%16, %17, %18, %19}, "
    "da, db, p, 1, 1, 1, 1;\n}\n"
    : "+f"(d[0]), "+f"(d[1]), "+f"(d[2]), "+f"(d[3]), "+f"(d[4]), "+f"(d[5]), "+f"(d[6]), "+f"(d[7]),
      "+f"(d[8]), "+f"(d[9]), "+f"(d[10]), "+f"(d[11]), "+f"(d[12]), "+f"(d[13]), "+f"(d[14]), "+f"(d[15]),
      "+f"(d[16]), "+f"(d[17]), "+f"(d[18]), "+f"(d[19])
    : "r"(la), "r"(lb), "n"(HA), "n"(HB));
}
template <uint32_t HA, uint32_t HB>
__device__ __forceinline__ void wgmma_ss_n40_tb_ta_z(float (&d)[20], uint32_t la, uint32_t lb) {
  asm volatile("{\n.reg .pred p;\n.reg .b64 da, db;\n"
    "mov.b64 da, {%20, %22};\nmov.b64 db, {%21, %23};\n"
    "setp.ne.b32 p, 0, 0;\n"
    "wgmma.mma_async.sync.aligned.m64n40k16.f32.bf16.bf16 "
    "{%0, %1, %2, %3, %4, %5, %6, %7, %8, %9, %10, %11, %12, %13, %14, %15, "
    "%16, %17, %18, %19}, "
    "da, db, p, 1, 1, 1, 1;\n}\n"
    : "=f"(d[0]), "=f"(d[1]), "=f"(d[2]), "=f"(d[3]), "=f"(d[4]), "=f"(d[5]), "=f"(d[6]), "=f"(d[7]),
      "=f"(d[8]), "=f"(d[9]), "=f"(d[10]), "=f"(d[11]), "=f"(d[12]), "=f"(d[13]), "=f"(d[14]), "=f"(d[15]),
      "=f"(d[16]), "=f"(d[17]), "=f"(d[18]), "=f"(d[19])
    : "r"(la), "r"(lb), "n"(HA), "n"(HB));
}
template <uint32_t HB>
__device__ __forceinline__ void wgmma_rs_n40_tb(float (&d)[20], uint32_t a0, uint32_t a1, uint32_t a2, uint32_t a3, uint32_t lb) {
  asm volatile("{\n.reg .pred p;\n.reg .b64 db;\n"
    "mov.b64 db, {%24, %25};\n"
    "setp.ne.b32 p, 1, 0;\n"
    "wgmma.mma_async.sync.aligned.m64n40k16.f32.bf16.bf16 "
    "{%0, %1, %2, %3, %4, %5, %6, %7, %8, %9, %10, %11, %12, %13, %14, %15, "
    "%16, %17, %18, %19}, "
    "{%20, %21, %22, %23}, db, p, 1, 1, 1;\n}\n"
    : "+f"(d[0]), "+f"(d[1]), "+f"(d[2]), "+f"(d[3]), "+f"(d[4]), "+f"(d[5]), "+f"(d[6]), "+f"(d[7]),
      "+f"(d[8]), "+f"(d[9]), "+f"(d[10]), "+f"(d[11]), "+f"(d[12]), "+f"(d[13]), "+f"(d[14]), "+f"(d[15]),
      "+f"(d[16]), "+f"(d[17]), "+f"(d[18]), "+f"(d[19])
    : "r"(a0), "r"(a1), "r"(a2), "r"(a3), "r"(lb), "n"(HB));
}
template <uint32_t HB>
__device__ __forceinline__ void wgmma_rs_n40_tb_z(float (&d)[20], uint32_t a0, uint32_t a1, uint32_t a2, uint32_t a3, uint32_t lb) {
  asm volatile("{\n.reg .pred p;\n.reg .b64 db;\n"
    "mov.b64 db, {%24, %25};\n"
    "setp.ne.b32 p, 0, 0;\n"
    "wgmma.mma_async.sync.aligned.m64n40k16.f32.bf16.bf16 "
    "{%0, %1, %2, %3, %4, %5, %6, %7, %8, %9, %10, %11, %12, %13, %14, %15, "
    "%16, %17, %18, %19}, "
    "{%20, %21, %22, %23}, db, p, 1, 1, 1;\n}\n"
    : "=f"(d[0]), "=f"(d[1]), "=f"(d[2]), "=f"(d[3]), "=f"(d[4]), "=f"(d[5]), "=f"(d[6]), "=f"(d[7]),
      "=f"(d[8]), "=f"(d[9]), "=f"(d[10]), "=f"(d[11]), "=f"(d[12]), "=f"(d[13]), "=f"(d[14]), "=f"(d[15]),
      "=f"(d[16]), "=f"(d[17]), "=f"(d[18]), "=f"(d[19])
    : "r"(a0), "r"(a1), "r"(a2), "r"(a3), "r"(lb), "n"(HB));
}
template <uint32_t HB>
__device__ __forceinline__ void wgmma_rs_n32(float (&d)[16], uint32_t a0, uint32_t a1, uint32_t a2, uint32_t a3, uint32_t lb) {
  asm volatile("{\n.reg .pred p;\n.reg .b64 db;\n"
    "mov.b64 db, {%20, %21};\n"
    "setp.ne.b32 p, 1, 0;\n"
    "wgmma.mma_async.sync.aligned.m64n32k16.f32.bf16.bf16 "
    "{%0, %1, %2, %3, %4, %5, %6, %7, %8, %9, %10, %11, %12, %13, %14, %15}, "
    "{%16, %17, %18, %19}, db, p, 1, 1, 0;\n}\n"
    : "+f"(d[0]), "+f"(d[1]), "+f"(d[2]), "+f"(d[3]), "+f"(d[4]), "+f"(d[5]), "+f"(d[6]), "+f"(d[7]),
      "+f"(d[8]), "+f"(d[9]), "+f"(d[10]), "+f"(d[11]), "+f"(d[12]), "+f"(d[13]), "+f"(d[14]), "+f"(d[15])
    : "r"(a0), "r"(a1), "r"(a2), "r"(a3), "r"(lb), "n"(HB));
}
template <uint32_t HB>
__device__ __forceinline__ void wgmma_rs_n32_z(float (&d)[16], uint32_t a0, uint32_t a1, uint32_t a2, uint32_t a3, uint32_t lb) {
  asm volatile("{\n.reg .pred p;\n.reg .b64 db;\n"
    "mov.b64 db, {%20, %21};\n"
    "setp.ne.b32 p, 0, 0;\n"
    "wgmma.mma_async.sync.aligned.m64n32k16.f32.bf16.bf16 "
    "{%0, %1, %2, %3, %4, %5, %6, %7, %8, %9, %10, %11, %12, %13, %14, %15}, "
    "{%16, %17, %18, %19}, db, p, 1, 1, 0;\n}\n"
    : "=f"(d[0]), "=f"(d[1]), "=f"(d[2]), "=f"(d[3]), "=f"(d[4]), "=f"(d[5]), "=f"(d[6]), "=f"(d[7]),
      "=f"(d[8]), "=f"(d[9]), "=f"(d[10]), "=f"(d[11]), "=f"(d[12]), "=f"(d[13]), "=f"(d[14]), "=f"(d[15])
    : "r"(a0), "r"(a1), "r"(a2), "r"(a3), "r"(lb), "n"(HB));
}
template <uint32_t HB>
__device__ __forceinline__ void wgmma_rs_n64(float (&d)[32], uint32_t a0, uint32_t a1, uint32_t a2, uint32_t a3, uint32_t lb) {
  asm volatile("{\n.reg .pred p;\n.reg .b64 db;\n"
    "mov.b64 db, {%36, %37};\n"
    "setp.ne.b32 p, 1, 0;\n"
    "wgmma.mma_async.sync.aligned.m64n64k16.f32.bf16.bf16 "
    "{%0, %1, %2, %3, %4, %5, %6, %7, %8, %9, %10, %11, %12, %13, %14, %15, "
    "%16, %17, %18, %19, %20, %21, %22, %23, %24, %25, %26, %27, %28, %29, %30, %31}, "
    "{%32, %33, %34, %35}, db, p, 1, 1, 0;\n}\n"
    : "+f"(d[0]), "+f"(d[1]), "+f"(d[2]), "+f"(d[3]), "+f"(d[4]), "+f"(d[5]), "+f"(d[6]), "+f"(d[7]),
      "+f"(d[8]), "+f"(d[9]), "+f"(d[10]), "+f"(d[11]), "+f"(d[12]), "+f"(d[13]), "+f"(d[14]), "+f"(d[15]),
      "+f"(d[16]), "+f"(d[17]), "+f"(d[18]), "+f"(d[19]), "+f"(d[20]), "+f"(d[21]), "+f"(d[22]), "+f"(d[23]),
      "+f"(d[24]), "+f"(d[25]), "+f"(d[26]), "+f"(d[27]), "+f"(d[28]), "+f"(d[29]), "+f"(d[30]), "+f"(d[31])
    : "r"(a0), "r"(a1), "r"(a2), "r"(a3), "r"(lb), "n"(HB));
}
template <uint32_t HB>
__device__ __forceinline__ void wgmma_rs_n64_z(float (&d)[32], uint32_t a0, uint32_t a1, uint32_t a2, uint32_t a3, uint32_t lb) {
  asm volatile("{\n.reg .pred p;\n.reg .b64 db;\n"
    "mov.b64 db, {%36, %37};\n"
    "setp.ne.b32 p, 0, 0;\n"
    "wgmma.mma_async.sync.aligned.m64n64k16.f32.bf16.bf16 "
    "{%0, %1, %2, %3, %4, %5, %6, %7, %8, %9, %10, %11, %12, %13, %14, %15, "
    "%16, %17, %18, %19, %20, %21, %22, %23, %24, %25, %26, %27, %28, %29, %30, %31}, "
    "{%32, %33, %34, %35}, db, p, 1, 1, 0;\n}\n"
    : "=f"(d[0]), "=f"(d[1]), "=f"(d[2]), "=f"(d[3]), "=f"(d[4]), "=f"(d[5]), "=f"(d[6]), "=f"(d[7]),
      "=f"(d[8]), "=f"(d[9]), "=f"(d[10]), "=f"(d[11]), "=f"(d[12]), "=f"(d[13]), "=f"(d[14]), "=f"(d[15]),
      "=f"(d[16]), "=f"(d[17]), "=f"(d[18]), "=f"(d[19]), "=f"(d[20]), "=f"(d[21]), "=f"(d[22]), "=f"(d[23]),
      "=f"(d[24]), "=f"(d[25]), "=f"(d[26]), "=f"(d[27]), "=f"(d[28]), "=f"(d[29]), "=f"(d[30]), "=f"(d[31])
    : "r"(a0), "r"(a1), "r"(a2), "r"(a3), "r"(lb), "n"(HB));
}

constexpr int SEQ = 2048, DM = 1024, NH = 32;
constexpr int NPAIR = 64;
constexpr int MAXT = 8;
constexpr int NITEM = 4;

constexpr float LOG2E = 1.4426950408889634f;
constexpr float QSCALE = 0.17677669529663687f * LOG2E;

__device__ __align__(1024) uint8_t g_qkv[3 * NH * SEQ * 64];
__device__ __align__(1024) uint8_t g_o[2 * 16 * NH * 8192];
__device__ __align__(16) float g_stats[3 * NH * 128];
__device__ __align__(128) float g_kv[NH * 32 * 40];
__device__ __align__(128) uint32_t g_kvb[NH * 640];

enum { C_AKV = 0, C_ATT = 16, C_BKV = 32, C_KVB = 48, C_AQ = 64, C_BQ = 128, C_NUM = 136 };
__device__ uint32_t g_cnt[C_NUM * 8];
__device__ uint32_t g_epoch, g_started;

enum { T_AKV = 0, T_AQ = 1, T_BKV = 2, T_BQ = 3, T_BOUT = 4, T_AOUT = 5 };

struct MegaParams {
  CUtensorMap x[2];
  CUtensorMap wkv[2];
  CUtensorMap wblk[4];
  CUtensorMap out;
  uint16_t gt[NPAIR][MAXT];
  uint8_t at[NPAIR][NITEM];
};
struct Tile { int type, idx, mp; };
__device__ __forceinline__ Tile decode_tile(uint32_t e) { return Tile{(int)(e & 7), (int)((e >> 3) & 15), (int)(e >> 7)}; }

constexpr int G_STAGES = 4;
constexpr int G_STAGE = 32768;
constexpr int S_STG = G_STAGES * G_STAGE;
constexpr int KV_STAGES = 3;
constexpr int S_KV = S_STG + 32768;
constexpr int S_OST = S_KV + KV_STAGES * 16384;
constexpr int S_ONES = S_OST + 8192;
constexpr int S_STAT = S_ONES + 1024;
constexpr int S_BAR = S_STAT + 128;
constexpr int G_STAGES0 = 6;
constexpr int B_GFULL = S_BAR, B_GEMPTY = B_GFULL + 8 * G_STAGES0;
constexpr int B_T0DONE = B_GEMPTY + 8 * G_STAGES0, B_LFREE = B_T0DONE + 8, B_ADONE = B_LFREE + 8;
constexpr int B_KFULL = B_ADONE + 8, B_KEMPTY = B_KFULL + 8 * KV_STAGES;
constexpr int B_SFULL = B_KEMPTY + 8 * KV_STAGES, B_SFREE = B_SFULL + 8;
constexpr int B_OFULL = B_SFREE + 8, B_OFREE = B_OFULL + 16;
constexpr int B_RDY = B_OFREE + 16, B_VERD = B_RDY + 8;
constexpr int S_FAST = B_VERD + 8;
constexpr int S_EPOCH = S_FAST + 4 * 2 * NITEM;
constexpr int MEGA_SMEM = S_EPOCH + 16 + 1024;
static_assert(MEGA_SMEM <= 232448, "shared memory");

constexpr int REGS_P = 72, REGS_A = 120, REGS_G = 200;

__device__ __forceinline__ uint32_t ld_counter(int c) {
  uint32_t v;
  asm volatile("ld.relaxed.gpu.global.u32 %0, [%1];" : "=r"(v) : "l"(g_cnt + c * 8) : "memory");
  return v;
}
__device__ __forceinline__ void cnt_wait2(int c0, uint32_t t0, int c1, uint32_t t1, uint32_t epoch) {
  const uint32_t w0 = epoch * t0 + t0, w1 = epoch * t1 + t1;
  uint32_t spins = 0;
  while (true) {
    const uint32_t a = ld_counter(c0), b = ld_counter(c1);
    if ((int32_t)(a - w0) >= 0 && (int32_t)(b - w1) >= 0) break;
    __nanosleep(40);
    if (++spins > (1u << 22)) __trap();
  }
}
__device__ __forceinline__ void cnt_wait(int c, uint32_t target, uint32_t epoch) {
  const uint32_t want = epoch * target + target;
  uint32_t spins = 0;
  while ((int32_t)(ld_counter(c) - want) < 0) {
    __nanosleep(40);
    if (++spins > (1u << 22)) __trap();
  }
}
__device__ __forceinline__ uint32_t cnt_add(int c) {
  uint32_t old;
  asm volatile("atom.add.relaxed.gpu.global.u32 %0, [%1], 1;" : "=r"(old) : "l"(g_cnt + c * 8) : "memory");
  return old;
}
__device__ __forceinline__ void cnt_red(int c, uint32_t v) {
  asm volatile("red.add.relaxed.gpu.global.u32 [%0], %1;" ::"l"(g_cnt + c * 8), "r"(v) : "memory");
}

template <int N> struct Ring {
  int slot; uint32_t phase;
  __device__ __forceinline__ void advance() { if (++slot == N) { slot = 0; phase ^= 1; } }
  __device__ __forceinline__ Ring next() const { Ring r = *this; r.advance(); return r; }
};
using KvRing = Ring<KV_STAGES>;

template <class Release, class Tail>
__device__ __forceinline__ void attn_item_fast(float (&o)[20], const uint32_t (&q)[8], uint32_t sb, KvRing& r, Release&& release, Tail&& tail_hook) {
  constexpr int EARLY = 4;
  constexpr uint32_t SOFF = 128;
  float S[2][16];
  uint32_t P[2][8];
  const uint32_t kd0 = desc_lo(sb + S_KV, 16), vd0 = desc_lo(sb + S_KV + 8192, (uint32_t)(S_ONES - S_KV - 8192));
  auto qk = [&](float (&s)[16], uint32_t off) {
    wgmma_rs_n32_z<HI_SW64_512>(s, q[0], q[1], q[2], q[3], kd0 + off);
    wgmma_rs_n32<HI_SW64_512>(s, q[4], q[5], q[6], q[7], kd0 + off + 2);
  };
  auto pv = [&](const uint32_t (&p)[8], uint32_t off) {
    const uint32_t d0 = vd0 + off - (off << 16);
    wgmma_rs_n40_tb<HI_SW64_512>(o, p[0], p[1], p[2], p[3], d0);
    wgmma_rs_n40_tb<HI_SW64_512>(o, p[4], p[5], p[6], p[7], d0 + 64u - (64u << 16));
  };
  wg_fence();
  qk(S[0], (uint32_t)r.slot * 1024u);
  wg_commit();
  wg_commit();
  int prev_slot = -1;
  auto step = [&](auto uc, auto issue_c, auto first_c, const KvRing& nx) {
    constexpr int u = decltype(uc)::value;
    constexpr bool issue = decltype(issue_c)::value, first = decltype(first_c)::value;
    const uint32_t a0 = (uint32_t)r.slot * 1024u;
    if constexpr (issue) {
      if constexpr (u == 3) mbar_wait(sb + B_KFULL + 8 * nx.slot, nx.phase);
      wg_fence();
      qk(S[(u + 1) & 1], u == 3 ? (uint32_t)nx.slot * 1024u : a0 + (u + 1) * SOFF);
    }
    wg_commit();
    wg_wait<1>();
    fence_regs(S[u & 1]);
    if constexpr (u == 1) { if (prev_slot >= 0) release(prev_slot); }
    float e[EARLY];
#pragma unroll
    for (int i = 0; i < EARLY; i++) e[i] = ex2_ordered(S[u & 1][i]);
    if constexpr (!first) {
      wg_fence();
      pv(P[(u + 1) & 1], u == 0 ? (uint32_t)prev_slot * 1024u + 3 * SOFF : a0 + (u - 1) * SOFF);
    }
    wg_commit();
#pragma unroll
    for (int i = 0; i < EARLY / 2; i++) P[u & 1][i] = pack_bf16(e[2 * i], e[2 * i + 1]);
#pragma unroll
    for (int i = EARLY / 2; i < 8; i++) P[u & 1][i] = pack_bf16(ex2_approx(S[u & 1][2 * i]), ex2_approx(S[u & 1][2 * i + 1]));
  };
  {
    const KvRing nx = r.next();
    static_for<4>([&](auto uc) {
      constexpr bool first = decltype(uc)::value == 0;
      step(uc, std::true_type{}, std::integral_constant<bool, first>{}, nx);
    });
    prev_slot = r.slot;
    r = nx;
  }
#pragma unroll 1
  for (int st = 1; st < 15; st++) {
    const KvRing nx = r.next();
    static_for<4>([&](auto uc) { step(uc, std::true_type{}, std::false_type{}, nx); });
    prev_slot = r.slot;
    r = nx;
  }
  tail_hook();
  static_for<4>([&](auto uc) {
    constexpr bool more = decltype(uc)::value != 3;
    step(uc, std::integral_constant<bool, more>{}, std::false_type{}, r);
  });
  wg_fence();
  pv(P[1], (uint32_t)r.slot * 1024u + 3 * SOFF);
  wg_commit();
  wg_wait<0>();
  release(r.slot);
  r.advance();
  fence_regs(o);
}

template <class Release, class Tail>
__device__ __forceinline__ void attn_item_safe(float (&o)[20], const uint32_t (&q)[8], uint32_t sb, KvRing& r, Release&& release, Tail&& tail_hook) {
  float m0 = -INFINITY, m1 = -INFINITY;
#pragma unroll 1
  for (int j = 0; j < 32; j++) {
    if (j == 30) tail_hook();
    if ((j & 1) == 0) mbar_wait(sb + B_KFULL + 8 * r.slot, r.phase);
    const uint32_t cur = sb + S_KV + r.slot * 16384 + (j & 1) * 4096;
    float s[32];
    uint32_t p[16];
    wg_fence();
    wgmma_rs_n64_z<HI_SW64_512>(s, q[0], q[1], q[2], q[3], desc_lo(cur, 16));
    wgmma_rs_n64<HI_SW64_512>(s, q[4], q[5], q[6], q[7], desc_lo(cur, 16) + 2);
    wg_commit();
    wg_wait<0>();
    fence_regs(s);
    float n0 = m0, n1 = m1;
#pragma unroll
    for (int i = 0; i < 8; i++) {
      n0 = fmaxf(n0, fmaxf(s[4 * i], s[4 * i + 1]));
      n1 = fmaxf(n1, fmaxf(s[4 * i + 2], s[4 * i + 3]));
    }
    n0 = fmaxf(n0, __shfl_xor_sync(0xffffffffu, n0, 1));
    n1 = fmaxf(n1, __shfl_xor_sync(0xffffffffu, n1, 1));
    n0 = fmaxf(n0, __shfl_xor_sync(0xffffffffu, n0, 2));
    n1 = fmaxf(n1, __shfl_xor_sync(0xffffffffu, n1, 2));
    const float c0 = exp2f(m0 - n0), c1 = exp2f(m1 - n1);
    m0 = n0; m1 = n1;
#pragma unroll
    for (int i = 0; i < 5; i++) { o[4 * i] *= c0; o[4 * i + 1] *= c0; o[4 * i + 2] *= c1; o[4 * i + 3] *= c1; }
#pragma unroll
    for (int i = 0; i < 8; i++) {
      p[2 * i] = pack_bf16(ex2_approx(s[4 * i] - m0), ex2_approx(s[4 * i + 1] - m0));
      p[2 * i + 1] = pack_bf16(ex2_approx(s[4 * i + 2] - m1), ex2_approx(s[4 * i + 3] - m1));
    }
    fence_regs(o);
    wg_fence();
    const uint32_t v = cur + 8192;
    const uint32_t d0 = desc_lo(v, sb + S_ONES - v);
#pragma unroll
    for (int k = 0; k < 4; k++)
      wgmma_rs_n40_tb<HI_SW64_512>(o, p[4 * k], p[4 * k + 1], p[4 * k + 2], p[4 * k + 3], d0 + 64u * k - ((64u * k) << 16));
    wg_commit();
    wg_wait<0>();
    fence_regs(o);
    if (j & 1) { release(r.slot); r.advance(); }
  }
}

struct GPipe {
  int slot; uint32_t mask;
  __device__ __forceinline__ uint32_t parity() const { return (mask >> slot) & 1u; }
  __device__ __forceinline__ void advance(int n) { mask ^= 1u << slot; slot = slot + 1 >= n ? 0 : slot + 1; }
};
__device__ __forceinline__ uint32_t g_slot_off(int slot) {
  return slot < G_STAGES ? (uint32_t)slot * G_STAGE : (slot == G_STAGES ? (uint32_t)S_STG : (uint32_t)S_KV);
}
template <bool AIMG, int WAIT, int NST, int KT0, int KT1>
__device__ __forceinline__ void gemm_stages(float (&a0)[64], float (&a1)[64], uint32_t sb, GPipe& r, int tid) {
  constexpr uint32_t HA = AIMG ? HI_SW64_512 : HI_SW128_1024;
  constexpr uint32_t MH = AIMG ? 256 : 512;
  const uint32_t da0 = desc_lo(sb, 16), db0 = desc_lo(sb + 16384, 4096);
  int prev = r.slot;
  auto release = [&](int s) { mbar_arrive_pair(sb + B_GEMPTY + 8 * s, tid); };
  auto stage = [&](auto first_c, auto head_c) {
    constexpr bool first = decltype(first_c)::value;
    constexpr bool head = decltype(head_c)::value;
    mbar_wait(sb + B_GFULL + 8 * r.slot, r.parity());
    const uint32_t off = (NST == G_STAGES ? (uint32_t)r.slot * G_STAGE : g_slot_off(r.slot)) >> 4;
    static_for<4>([&](auto kc) {
      constexpr int ks = decltype(kc)::value;
      const uint32_t da = da0 + off + (AIMG ? (ks >> 1) * 512 + (ks & 1) * 2 : ks * 2);
      const uint32_t db = db0 + off + (ks >> 1) * 512 + (ks & 1) * 128;
      wg_fence();
      if constexpr (first && ks == 0) {
        wgmma_ss_n128_tb_z<HA, HI_SW128_1024>(a0, da, db);
        wgmma_ss_n128_tb_z<HA, HI_SW128_1024>(a1, da + MH, db);
      } else {
        wgmma_ss_n128_tb<HA, HI_SW128_1024>(a0, da, db);
        wgmma_ss_n128_tb<HA, HI_SW128_1024>(a1, da + MH, db);
      }
      wg_commit();
      wg_wait<WAIT>();
      if constexpr (WAIT == 1 && ks == 0 && !head) release(prev);
    });
    if constexpr (WAIT == 0) release(r.slot);
    prev = r.slot;
    r.advance(NST);
  };
  stage(std::integral_constant<bool, KT0 == 0>{}, std::true_type{});
#pragma unroll 1
  for (int kt = KT0 + 1; kt < KT1; kt++) stage(std::false_type{}, std::false_type{});
  if constexpr (WAIT == 1) { wg_wait<0>(); release(prev); }
}

__device__ __forceinline__ void stage_slot(uint32_t stg, int s, int m, int wq, int lane, const uint32_t (&p)[8]) {
  const int row = m * 64 + wq * 16 + (lane & 7) + ((lane >> 3) & 1) * 8;
  const uint32_t a = stg + s * 8192 + row * 64;
  const int sw = (row >> 1) & 3, ch = lane >> 4;
  stmatrix_x4(a + ((ch ^ sw) << 4), p[0], p[1], p[2], p[3]);
  stmatrix_x4(a + (((ch + 2) ^ sw) << 4), p[4], p[5], p[6], p[7]);
}
__device__ __forceinline__ void stage_slot_box(uint32_t stg, int s, int m, int wq, int lane, const uint32_t (&p)[8]) {
  const int row = m * 64 + wq * 16 + (lane & 7) + ((lane >> 3) & 1) * 8;
  const uint32_t a = stg + (s >> 1) * 16384 + row * 128;
  const int sw = row & 7, ch = (s & 1) * 4 + (lane >> 4);
  stmatrix_x4(a + ((ch ^ sw) << 4), p[0], p[1], p[2], p[3]);
  stmatrix_x4(a + (((ch + 2) ^ sw) << 4), p[4], p[5], p[6], p[7]);
}
__device__ __forceinline__ float phi_fn(float t) {
  const float e = ex2_approx(t * LOG2E);
  const float y = t > 0.f ? t + 1.f : e;
  return y + 1e-6f;
}

__device__ __forceinline__ void gemm_tile(const Tile& t, int i, uint32_t sb, uint8_t* smem, GPipe& r, int warp, int lane) {
  const int wq = warp & 3, tid = threadIdx.x & 127;
  const int qd = lane & 3, r8 = lane >> 2;
  const uint32_t stg = sb + S_STG;
  float a0[64], a1[64];
  if (i == 0) {
    gemm_stages<false, 1, G_STAGES0, 0, 16>(a0, a1, sb, r, tid);
    r.slot = 0;
    mbar_arrive_pair(sb + B_T0DONE, tid);
  } else if (t.type == T_AOUT) {
    gemm_stages<true, 1, G_STAGES, 0, 8>(a0, a1, sb, r, tid);
    if (t.mp < 4) gemm_stages<true, 1, G_STAGES, 8, 16>(a0, a1, sb, r, tid);
    else gemm_stages<true, 1, G_STAGES0, 8, 16>(a0, a1, sb, r, tid);
  } else if (t.type == T_BOUT) {
    gemm_stages<true, 1, G_STAGES, 0, 16>(a0, a1, sb, r, tid);
  } else {
    gemm_stages<false, 0, G_STAGES, 0, 16>(a0, a1, sb, r, tid);
  }
  fence_regs(a0); fence_regs(a1);
  if (i > 0) mbar_wait(sb + B_SFREE, (i - 1) & 1);

  if (t.type <= T_AQ) {
    const float sc = t.type == T_AQ ? QSCALE : 1.f;
    float* stat = reinterpret_cast<float*>(smem + S_STAT);
    static_for<4>([&](auto sc_) {
      constexpr int s = decltype(sc_)::value;
      static_for<2>([&](auto mc) {
        constexpr int m = decltype(mc)::value;
        float (&a)[64] = m == 0 ? a0 : a1;
        float s0 = 0.f, s1 = 0.f;
        uint32_t p[8];
#pragma unroll
        for (int j = 0; j < 4; j++) {
          const int b = (s * 4 + j) * 4;
          const float x0 = a[b] * sc, x1 = a[b + 1] * sc, x2 = a[b + 2] * sc, x3 = a[b + 3] * sc;
          s0 = fmaf(x0, x0, s0); s0 = fmaf(x1, x1, s0);
          s1 = fmaf(x2, x2, s1); s1 = fmaf(x3, x3, s1);
          p[2 * j] = pack_bf16(x0, x1);
          p[2 * j + 1] = pack_bf16(x2, x3);
        }
        stage_slot(stg, s, m, wq, lane, p);
        s0 += __shfl_xor_sync(0xffffffffu, s0, 1);
        s1 += __shfl_xor_sync(0xffffffffu, s1, 1);
        s0 += __shfl_xor_sync(0xffffffffu, s0, 2);
        s1 += __shfl_xor_sync(0xffffffffu, s1, 2);
        const uint32_t mx = __reduce_max_sync(0xffffffffu, max(__float_as_uint(s0), __float_as_uint(s1)));
        if (lane == 0) stat[s * 8 + m * 4 + wq] = __uint_as_float(mx);
        __syncwarp();
      });
    });
  } else if (t.type == T_BKV) {
    static_for<4>([&](auto sc_) {
      constexpr int s = decltype(sc_)::value;
      static_for<2>([&](auto mc) {
        constexpr int m = decltype(mc)::value;
        float (&a)[64] = m == 0 ? a0 : a1;
        uint32_t p[8];
#pragma unroll
        for (int j = 0; j < 4; j++) {
          const int b = (s * 4 + j) * 4;
          float x0 = a[b], x1 = a[b + 1], x2 = a[b + 2], x3 = a[b + 3];
          if constexpr (s < 2) { x0 = phi_fn(x0); x1 = phi_fn(x1); x2 = phi_fn(x2); x3 = phi_fn(x3); }
          p[2 * j] = pack_bf16(x0, x1);
          p[2 * j + 1] = pack_bf16(x2, x3);
        }
        stage_slot(stg, s, m, wq, lane, p);
      });
    });
    fence_proxy_async_smem();
    named_bar_sync(1, 128);
    float d[2][20];
    wg_fence();
    static_for<2>([&](auto hc) {
      constexpr int hh = decltype(hc)::value;
      const uint32_t tb = stg + (2 + hh) * 8192;
      const uint32_t la = desc_lo(stg, 8192), lb = desc_lo(tb, sb + S_ONES - tb);
      wgmma_ss_n40_tb_ta_z<HI_SW64_512, HI_SW64_512>(d[hh], la, lb);
#pragma unroll
      for (int k = 1; k < 8; k++)
        wgmma_ss_n40_tb_ta<HI_SW64_512, HI_SW64_512>(d[hh], la + 64u * k, lb + 64u * k - ((64u * k) << 16));
    });
    wg_commit();
    wg_wait<0>();
    named_bar_sync(1, 128);
    fence_regs(d[0]); fence_regs(d[1]);
    const int hh = wq >> 1;
    float* dst = reinterpret_cast<float*>(smem + S_STG + hh * 8192) + ((wq & 1) * 16 + r8) * 40 + 2 * qd;
#pragma unroll
    for (int j = 0; j < 5; j++) {
      *reinterpret_cast<float2*>(dst + 8 * j) = hh ? make_float2(d[1][4 * j], d[1][4 * j + 1]) : make_float2(d[0][4 * j], d[0][4 * j + 1]);
      *reinterpret_cast<float2*>(dst + 8 * 40 + 8 * j) = hh ? make_float2(d[1][4 * j + 2], d[1][4 * j + 3]) : make_float2(d[0][4 * j + 2], d[0][4 * j + 3]);
    }
  } else if (t.type == T_BQ) {
    uint32_t pq[2][4][8];
    static_for<4>([&](auto sc_) {
      constexpr int s = decltype(sc_)::value;
      static_for<2>([&](auto mc) {
        constexpr int m = decltype(mc)::value;
        float (&a)[64] = m == 0 ? a0 : a1;
#pragma unroll
        for (int j = 0; j < 4; j++) {
          const int b = (s * 4 + j) * 4;
          pq[m][s][2 * j] = pack_bf16(phi_fn(a[b]), phi_fn(a[b + 1]));
          pq[m][s][2 * j + 1] = pack_bf16(phi_fn(a[b + 2]), phi_fn(a[b + 3]));
        }
      });
    });
    mbar_wait(sb + B_GFULL + 8 * r.slot, r.parity());
    const uint32_t kvd = desc_lo(sb + r.slot * G_STAGE, 640);
    static_for<2>([&](auto pc) {
      constexpr int sp = decltype(pc)::value;
      float d[2][2][20];
      wg_fence();
      static_for<2>([&](auto sc_) {
        constexpr int ss = decltype(sc_)::value, s = 2 * sp + ss;
        static_for<2>([&](auto mc) {
          constexpr int m = decltype(mc)::value;
          wgmma_rs_n40_tb_z<HI_NOSW_128>(d[ss][m], pq[m][s][0], pq[m][s][1], pq[m][s][2], pq[m][s][3], kvd + s * 160);
          wgmma_rs_n40_tb<HI_NOSW_128>(d[ss][m], pq[m][s][4], pq[m][s][5], pq[m][s][6], pq[m][s][7], kvd + s * 160 + 80);
        });
      });
      wg_commit();
      wg_wait<0>();
      static_for<2>([&](auto sc_) {
        constexpr int ss = decltype(sc_)::value, s = 2 * sp + ss;
        static_for<2>([&](auto mc) {
          constexpr int m = decltype(mc)::value;
          fence_regs(d[ss][m]);
          const float i0 = rcp_approx(d[ss][m][16] + 1e-6f), i1 = rcp_approx(d[ss][m][18] + 1e-6f);
          uint32_t p[8];
#pragma unroll
          for (int j = 0; j < 4; j++) {
            p[2 * j] = pack_bf16(d[ss][m][4 * j] * i0, d[ss][m][4 * j + 1] * i0);
            p[2 * j + 1] = pack_bf16(d[ss][m][4 * j + 2] * i1, d[ss][m][4 * j + 3] * i1);
          }
          stage_slot(stg, s, m, wq, lane, p);
        });
      });
    });
    mbar_arrive_pair(sb + B_GEMPTY + 8 * r.slot, tid);
    r.advance(G_STAGES);
  } else {
    static_for<4>([&](auto sc_) {
      constexpr int s = decltype(sc_)::value;
      static_for<2>([&](auto mc) {
        constexpr int m = decltype(mc)::value;
        float (&a)[64] = m == 0 ? a0 : a1;
        uint32_t p[8];
#pragma unroll
        for (int j = 0; j < 4; j++) {
          const int b = (s * 4 + j) * 4;
          p[2 * j] = pack_bf16(a[b], a[b + 1]);
          p[2 * j + 1] = pack_bf16(a[b + 2], a[b + 3]);
        }
        stage_slot_box(stg, s, m, wq, lane, p);
      });
    });
  }
}

__global__ void __cluster_dims__(2, 1, 1) __launch_bounds__(512, 1)
concat_heads_mha_linattn_kernel(const __grid_constant__ MegaParams prm) {
  extern __shared__ uint8_t smem_raw[];
  const uint32_t sb = (smem_u32(smem_raw) + 1023) & ~1023u;
  uint8_t* smem = smem_raw + (sb - smem_u32(smem_raw));
  const int warp = uniform_warp_id(), lane = threadIdx.x & 31;
  const uint32_t rank = cluster_rank();
  const int pair = blockIdx.x >> 1;

  if (threadIdx.x == 64) { prefetch_tmap(&prm.x[0]); prefetch_tmap(&prm.wkv[0]); prefetch_tmap(&prm.wblk[0]); }
  if (threadIdx.x == 0) {
    for (int s = 0; s < G_STAGES0; s++) { mbar_init(sb + B_GFULL + 8 * s, 1); mbar_init(sb + B_GEMPTY + 8 * s, 2); }
    mbar_init(sb + B_T0DONE, 2); mbar_init(sb + B_LFREE, 2); mbar_init(sb + B_ADONE, 4);
    for (int s = 0; s < KV_STAGES; s++) { mbar_init(sb + B_KFULL + 8 * s, 1); mbar_init(sb + B_KEMPTY + 8 * s, 4); }
    mbar_init(sb + B_SFULL, 128); mbar_init(sb + B_SFREE, 1);
    for (int w = 0; w < 2; w++) { mbar_init(sb + B_OFULL + 8 * w, 128); mbar_init(sb + B_OFREE + 8 * w, 1); }
    mbar_init(sb + B_RDY, 1); mbar_init(sb + B_VERD, 1);
    fence_mbar_init();
  }
  if (threadIdx.x == 32) *reinterpret_cast<volatile uint32_t*>(smem + S_EPOCH) = *reinterpret_cast<volatile uint32_t*>(&g_epoch);
  if (threadIdx.x < 256) reinterpret_cast<uint32_t*>(smem + S_ONES)[threadIdx.x] = 0x3F803F80u;
  fence_proxy_async_smem();
  __syncthreads();
  cluster_sync();

  if (warp < 4) {
    reg_dealloc<REGS_P>();
    const uint32_t epoch = *reinterpret_cast<volatile uint32_t*>(smem + S_EPOCH);
    if (warp == 0) {
      if (lane == 0) {
        GPipe r{0, 0xffffffffu};
        for (int i = 0; i < MAXT; i++) {
          const Tile t = decode_tile(prm.gt[pair][i]);
          const int rb = t.mp * 2 + (int)rank;
          const CUtensorMap* mw; int c0, c2;
          if (t.type == T_AKV || t.type == T_BKV) { mw = &prm.wkv[t.type == T_BKV]; c0 = 64 * t.idx; c2 = 1; }
          else { mw = &prm.wblk[t.type == T_AQ ? 0 : t.type == T_BQ ? 1 : t.type == T_BOUT ? 2 : 3]; c0 = 0; c2 = 2 * t.idx; }
          const bool isout = t.type >= T_BOUT;
          const CUtensorMap* ma = &prm.x[t.type <= T_AQ ? 0 : 1];
          const uint8_t* img = g_o + (size_t)((t.type == T_BOUT ? 16 : 0) + rb) * NH * 8192;
          const bool late = t.type == T_AOUT && t.mp >= 4;
          if (t.type == T_BOUT) cnt_wait(C_BQ + t.mp, 16, epoch);
          for (int kt = 0; kt < 16; kt++) {
            if (t.type == T_AOUT && (kt & 7) == 0) cnt_wait(C_ATT + t.mp * 2 + (kt >> 3), 64, epoch);
            if (late && kt == 8) {
              mbar_wait_long(sb + B_ADONE, 0);
              mbar_wait_long(sb + B_LFREE, 0);
            }
            mbar_wait(sb + B_GEMPTY + 8 * r.slot, r.parity());
            const uint32_t full = sb + B_GFULL + 8 * r.slot, sa = sb + g_slot_off(r.slot);
            mbar_expect_tx(full, G_STAGE);
            tma_load_3d_mc(sa + 16384 + rank * 8192, mw, full, c0, kt * 64 + (int)rank * 32, c2, (uint16_t)3);
            if (isout) bulk_load_1d(sa, img + kt * 16384, 16384, full);
            else tma_load_2d(sa, ma, full, kt * 64, rb * 128);
            r.advance((i == 0 || (late && kt >= 8)) ? G_STAGES0 : G_STAGES);
          }
          if (i == 0) r.slot = 0;
          if (t.type == T_BQ) {
            cnt_wait2(C_KVB + 2 * t.idx, 1, C_KVB + 2 * t.idx + 1, 1, epoch);
            mbar_wait_long(sb + B_GEMPTY + 8 * r.slot, r.parity());
            const uint32_t full = sb + B_GFULL + 8 * r.slot;
            mbar_expect_tx(full, 4 * 2560);
            bulk_load_1d(sb + r.slot * G_STAGE, g_kvb + t.idx * 4 * 640, 4 * 2560, full);
            r.advance(G_STAGES);
          }
        }
      }
    } else if (warp == 1) {
      KvRing r{0, 1};
      if (lane == 0) mbar_wait_long(sb + B_T0DONE, 0);
      for (int it = 0; it < NITEM; it++) {
        const int h = prm.at[pair][it] & 31, mp = prm.at[pair][it] >> 5;
        const uint8_t* src = g_qkv + (size_t)((1 + rank) * NH + h) * SEQ * 64;
        auto load_stage = [&](int j) {
          mbar_wait_long(sb + B_KEMPTY + 8 * r.slot, r.phase);
          const uint32_t full = sb + B_KFULL + 8 * r.slot;
          mbar_expect_tx(full, 16384);
          bulk_load_1d_mc(sb + S_KV + r.slot * 16384 + rank * 8192, src + j * 8192, 8192, full, (uint16_t)3);
          r.advance();
        };
        if (lane == 0) {
          cnt_wait2(C_AKV + (h >> 1), 16, C_AQ + (h >> 2) * 8 + mp, 2, epoch);
          mbar_arrive(sb + B_RDY);
          load_stage(0);
        }
        __syncwarp();
        {
          const uint4 kq = __ldcg(reinterpret_cast<const uint4*>(g_stats + (NH + h) * 128) + lane);
          const uint4 vq = __ldcg(reinterpret_cast<const uint4*>(g_stats + (2 * NH + h) * 128) + lane);
          const uint4 qq = __ldcg(reinterpret_cast<const uint4*>(g_stats + h * 128 + mp * 16 + rank * 8) + (lane & 1));
          const float km = __uint_as_float(__reduce_max_sync(0xffffffffu, max(max(kq.x, kq.y), max(kq.z, kq.w))));
          const float vm = __uint_as_float(__reduce_max_sync(0xffffffffu, max(max(vq.x, vq.y), max(vq.z, vq.w))));
          const float qm = __uint_as_float(max(max(qq.x, qq.y), max(qq.z, qq.w)));
          const bool ok = (qm * km <= 4000.f) && (vm <= 1.0e21f) && (vm >= 3.0e-17f);
          if (lane < 2) reinterpret_cast<volatile uint32_t*>(smem + S_FAST)[it * 2 + lane] = ok ? 1u : 0u;
          __syncwarp();
          if (lane == 0) mbar_arrive(sb + B_VERD);
        }
        if (lane == 0) { for (int j = 1; j < 16; j++) load_stage(j); }
        __syncwarp();
      }
    } else if (warp == 2) {
      const uint32_t stg = sb + S_STG;
      for (int i = 0; i < MAXT; i++) {
        const Tile t = decode_tile(prm.gt[pair][i]);
        const int rb = t.mp * 2 + (int)rank;
        uint32_t last = 0;
        if (lane == 0) {
          mbar_wait_long(sb + B_SFULL, i & 1);
          if (t.type <= T_AQ) {
            for (int s = 0; s < 4; s++) {
              const int ph = t.type == T_AQ ? 4 * t.idx + s : (1 + (s >> 1)) * NH + 2 * t.idx + (s & 1);
              bulk_store_1d(g_qkv + ((size_t)ph * SEQ + rb * 128) * 64, stg + s * 8192, 8192);
              bulk_store_1d(g_stats + ph * 128 + rb * 8, sb + S_STAT + s * 32, 32);
            }
          } else if (t.type == T_BKV) {
            for (int s = 0; s < 2; s++) bulk_reduce_add_f32(g_kv + (2 * t.idx + s) * 1280, stg + s * 8192, 5120);
          } else if (t.type == T_BQ) {
            bulk_store_1d(g_o + (size_t)((16 + rb) * NH + 4 * t.idx) * 8192, stg, 4 * 8192);
          } else {
            for (int s = 0; s < 2; s++) tma_store_2d(&prm.out, stg + s * 16384, (t.type == T_BOUT ? DM : 0) + t.idx * 128 + s * 64, rb * 128);
          }
          bulk_commit();
          bulk_wait_read<0>();
          mbar_arrive(sb + B_SFREE);
          if (i + 1 < MAXT && (prm.gt[pair][i + 1] & 7) == T_AOUT && (prm.gt[pair][i + 1] >> 7) >= 4) {
            mbar_arrive_cluster(sb + B_LFREE, 0); mbar_arrive_cluster(sb + B_LFREE, 1);
          }
          if (t.type < T_BOUT) {
            bulk_wait<0>();
            const int c = t.type == T_AKV ? C_AKV + t.idx : t.type == T_AQ ? C_AQ + t.idx * 8 + t.mp : t.type == T_BKV ? C_BKV + t.idx : C_BQ + t.mp;
            if (t.type == T_BKV) last = cnt_add(c) + 1 == epoch * 16 + 16 ? 1u : 0u;
            else cnt_red(c, 1);
          }
        }
        last = __shfl_sync(0xffffffffu, last, 0);
        if (last) {
          asm volatile("fence.acq_rel.gpu;" ::: "memory");
          fence_proxy_async_all();
#pragma unroll 2
          for (int c = lane; c < 320; c += 32) {
            const int hh = c / 160, rr = c % 160, d = rr / 5, g = rr % 5;
            float4* src = reinterpret_cast<float4*>(g_kv + (2 * t.idx + hh) * 1280 + d * 40 + g * 8);
            const float4 a = __ldcg(src), b = __ldcg(src + 1);
            uint4 v;
            v.x = pack_bf16(a.x, a.y); v.y = pack_bf16(a.z, a.w); v.z = pack_bf16(b.x, b.y); v.w = pack_bf16(b.z, b.w);
            *reinterpret_cast<uint4*>(g_kvb + (2 * t.idx + hh) * 640 + (d >> 3) * 160 + g * 32 + (d & 7) * 4) = v;
            __stcg(src, make_float4(0.f, 0.f, 0.f, 0.f)); __stcg(src + 1, make_float4(0.f, 0.f, 0.f, 0.f));
          }
          __threadfence();
          fence_proxy_async_all();
          __syncwarp();
          if (lane == 0) cnt_red(C_KVB + t.idx, 1);
        }
        __syncwarp();
      }
      if (lane == 0) bulk_wait_read<0>();
    } else {
      if (lane == 0) {
        if (atomicAdd(&g_started, 1u) == gridDim.x - 1) { g_started = 0; __threadfence(); atomicAdd(&g_epoch, 1u); }
        for (int it = 0; it < NITEM; it++) {
          const int h = prm.at[pair][it] & 31, mp = prm.at[pair][it] >> 5;
          uint8_t* dst = g_o + (size_t)((mp * 2 + rank) * NH + h) * 8192;
          for (int w = 0; w < 2; w++) {
            mbar_wait_long(sb + B_OFULL + 8 * w, it & 1);
            bulk_store_1d(dst + w * 4096, sb + S_OST + w * 4096, 4096);
            bulk_commit();
          }
          bulk_wait_read<0>();
          mbar_arrive(sb + B_OFREE); mbar_arrive(sb + B_OFREE + 8);
          bulk_wait<0>();
          cnt_red(C_ATT + mp * 2 + (h >> 4), 2);
        }
      }
    }
    __syncwarp();
    cluster_sync();
  } else if (warp < 12) {
    reg_dealloc<REGS_A>();
    const int wg = (warp >> 2) - 1, wq = warp & 3, tid = threadIdx.x & 127;
    const int qd = lane & 3, r8 = lane >> 2;
    auto release = [&](int slot) { mbar_arrive_pair(sb + B_KEMPTY + 8 * slot, tid); };
    auto load_q = [&](uint32_t (&q)[8], int it) {
      const int h = prm.at[pair][it] & 31, mp = prm.at[pair][it] >> 5;
      const int row = mp * 256 + (int)rank * 128 + wg * 64 + wq * 16 + r8;
      const uint8_t* qp = g_qkv + ((size_t)h * SEQ + row) * 64 + qd * 4;
      const int sw = (row >> 1) & 3;
#pragma unroll
      for (int ks = 0; ks < 2; ks++) {
        q[4 * ks + 0] = __ldcg(reinterpret_cast<const uint32_t*>(qp + (((2 * ks) ^ sw) << 4)));
        q[4 * ks + 1] = __ldcg(reinterpret_cast<const uint32_t*>(qp + (((2 * ks) ^ sw) << 4) + 512));
        q[4 * ks + 2] = __ldcg(reinterpret_cast<const uint32_t*>(qp + (((2 * ks + 1) ^ sw) << 4)));
        q[4 * ks + 3] = __ldcg(reinterpret_cast<const uint32_t*>(qp + (((2 * ks + 1) ^ sw) << 4) + 512));
      }
    };
    uint32_t q[8], qn[8];
    KvRing r{0, 0};
    mbar_wait(sb + B_RDY, 0);
    load_q(q, 0);
    for (int it = 0; it < NITEM; it++) {
      mbar_wait(sb + B_VERD, it & 1);
      mbar_wait(sb + B_KFULL + 8 * r.slot, r.phase);
      const bool fast = __all_sync(0xffffffffu, reinterpret_cast<volatile uint32_t*>(smem + S_FAST)[it * 2 + wg] != 0);
      float o[20];
#pragma unroll
      for (int i = 0; i < 20; i++) o[i] = 0.f;
      fence_regs(o);
      auto tail_hook = [&]() {
        if (it + 1 < NITEM) {
          mbar_wait(sb + B_RDY, (it + 1) & 1);
          load_q(qn, it + 1);
        }
      };
      if (fast) attn_item_fast(o, q, sb, r, release, tail_hook);
      else attn_item_safe(o, q, sb, r, release, tail_hook);
      const float i0 = rcp_approx(o[16]), i1 = rcp_approx(o[18]);
      uint32_t p[8];
#pragma unroll
      for (int j = 0; j < 4; j++) {
        p[2 * j] = pack_bf16(o[4 * j] * i0, o[4 * j + 1] * i0);
        p[2 * j + 1] = pack_bf16(o[4 * j + 2] * i1, o[4 * j + 3] * i1);
      }
      if (it > 0) mbar_wait(sb + B_OFREE + 8 * wg, (it - 1) & 1);
      stage_slot(sb + S_OST + wg * 4096, 0, 0, wq, lane, p);
      fence_proxy_async_smem();
      mbar_arrive(sb + B_OFULL + 8 * wg);
#pragma unroll
      for (int i = 0; i < 8; i++) q[i] = qn[i];
    }
    mbar_arrive_pair(sb + B_ADONE, tid);
    cluster_sync();
  } else {
    reg_alloc<REGS_G>();
    GPipe r{0, 0u};
    for (int i = 0; i < MAXT; i++) {
      const Tile t = decode_tile(__shfl_sync(0xffffffffu, (uint32_t)prm.gt[pair][i], 0));
      gemm_tile(t, i, sb, smem, r, warp, lane);
      fence_proxy_async_smem();
      mbar_arrive(sb + B_SFULL);
    }
    __syncwarp();
    cluster_sync();
  }
}

typedef CUresult (*PFN_encodeTiled)(CUtensorMap*, CUtensorMapDataType, cuuint32_t, void*, const cuuint64_t*, const cuuint64_t*,
                                    const cuuint32_t*, const cuuint32_t*, CUtensorMapInterleave, CUtensorMapSwizzle,
                                    CUtensorMapL2promotion, CUtensorMapFloatOOBfill);

static PFN_encodeTiled get_encode() {
  static PFN_encodeTiled fn = nullptr;
  if (!fn) {
    void* p = nullptr;
    cudaDriverEntryPointQueryResult q;
    cudaGetDriverEntryPoint("cuTensorMapEncodeTiled", &p, cudaEnableDefault, &q);
    fn = (PFN_encodeTiled)p;
  }
  return fn;
}
static void make_map(CUtensorMap* m, const void* base, int rank, const cuuint64_t* dims, const cuuint64_t* strides, const cuuint32_t* box) {
  cuuint32_t es[3] = {1, 1, 1};
  get_encode()(m, CU_TENSOR_MAP_DATA_TYPE_BFLOAT16, rank, const_cast<void*>(base), dims, strides, box, es, CU_TENSOR_MAP_INTERLEAVE_NONE,
               CU_TENSOR_MAP_SWIZZLE_128B, CU_TENSOR_MAP_L2_PROMOTION_L2_256B, CU_TENSOR_MAP_FLOAT_OOB_FILL_NONE);
}
static void map_2d(CUtensorMap* m, const void* base, int rows, int cols) {
  cuuint64_t dims[2] = {(cuuint64_t)cols, (cuuint64_t)rows};
  cuuint64_t strides[1] = {(cuuint64_t)cols * 2};
  cuuint32_t box[2] = {64, 128};
  make_map(m, base, 2, dims, strides, box);
}
static void map_parts(CUtensorMap* m, const void* base) {
  cuuint64_t dims[3] = {1024, 1024, 3};
  cuuint64_t strides[2] = {3072 * 2, 1024 * 2};
  cuuint32_t box[3] = {64, 32, 2};
  make_map(m, base, 3, dims, strides, box);
}
static void map_blk(CUtensorMap* m, const void* base, int N) {
  cuuint64_t dims[3] = {64, 1024, (cuuint64_t)(N / 64)};
  cuuint64_t strides[2] = {(cuuint64_t)N * 2, 128};
  cuuint32_t box[3] = {64, 32, 2};
  make_map(m, base, 3, dims, strides, box);
}

static void build_schedule(MegaParams& P) {
  auto enc = [](int type, int idx, int mp) { return (uint16_t)(type | (idx << 3) | (mp << 7)); };
  for (int p = 0; p < NPAIR; p++) {
    const int hi = p >> 3, lo = p & 7;
    int n = 0;
    P.gt[p][n++] = hi < 4 ? enc(T_AKV, hi, lo) : hi < 6 ? enc(T_AQ, hi - 4, lo) : enc(T_AKV, hi - 2, lo);
    P.gt[p][n++] = hi < 2 ? enc(T_AKV, 6 + hi, lo) : hi < 4 ? enc(T_AQ, hi, lo) : enc(T_AKV, 4 + hi, lo);
    P.gt[p][n++] = hi < 4 ? enc(T_AKV, 12 + hi, lo) : enc(T_AQ, hi, lo);
    P.gt[p][n++] = enc(T_BKV, hi, lo);
    P.gt[p][n++] = enc(T_BKV, 8 + hi, lo);
    P.gt[p][n++] = enc(T_BQ, hi, lo);
    if (p < 32) {
      P.gt[p][n++] = enc(T_AOUT, lo, hi);
      P.gt[p][n++] = enc(T_BOUT, lo, 4 + hi);
    } else {
      P.gt[p][n++] = enc(T_BOUT, lo, hi - 4);
      P.gt[p][n++] = enc(T_AOUT, lo, hi);
    }
    for (int r = 0; r < NITEM; r++) {
      const int h = r < 2 ? r * 8 + hi : 16 + (p & 15);
      const int mp = r < 2 ? lo : (r - 2) * 4 + (p >> 4);
      P.at[p][r] = (uint8_t)(h | (mp << 5));
    }
  }
}

extern "C" void kernel_launch(void* const* d_in, const int* in_sizes, int n_in, void* d_out, int out_size) {
  static bool attr_done = false;
  if (!attr_done) {
    attr_done = true;
    cudaFuncSetAttribute(concat_heads_mha_linattn_kernel, cudaFuncAttributeMaxDynamicSharedMemorySize, MEGA_SMEM);
  }
  MegaParams P;
  memset(&P, 0, sizeof(P));
  map_2d(&P.x[0], d_in[0], SEQ, DM);
  map_2d(&P.x[1], d_in[3], SEQ, DM);
  map_parts(&P.wkv[0], d_in[1]);
  map_parts(&P.wkv[1], d_in[4]);
  map_blk(&P.wblk[0], d_in[1], 3 * DM);
  map_blk(&P.wblk[1], d_in[4], 3 * DM);
  map_blk(&P.wblk[2], d_in[5], DM);
  map_blk(&P.wblk[3], d_in[2], DM);
  map_2d(&P.out, d_out, SEQ, 2 * DM);
  build_schedule(P);
  concat_heads_mha_linattn_kernel<<<2 * NPAIR, 512, MEGA_SMEM, cudaStreamPerThread>>>(P);
}
```
